```python
import torch

def _softmax(x, axis=-1):
    return torch.softmax(x, dim=axis)

def _gelu(x):
    return torch.nn.functional.gelu(x, approximate='tanh')

def _silu(x):
    return torch.nn.functional.silu(x)

def _sigmoid(x):
    return torch.sigmoid(x)

def _layernorm(x, axis=-1, eps=1e-05):
    m = x.mean(dim=axis, keepdim=True)
    v = x.var(dim=axis, keepdim=True, unbiased=False)
    return (x - m) / torch.sqrt(v + eps)

def _scatter_add(tgt, idx, src, axis=0):
    return tgt.clone().index_add_(axis, idx, src)

def _segment_sum(src, seg, n):
    out = torch.zeros((n,) + src.shape[1:], dtype=src.dtype)
    return out.index_add_(0, seg, src)

def _pad(x, pw):
    flat = tuple((v for pair in reversed(pw) for v in pair))
    return torch.nn.functional.pad(x, flat)
kernel_name = 'adaLN_cond__softmax_full_mha__dense_activation_silu__prompt'

def setup_inputs():

    _w = lambda a: (lambda t: t.to(torch.bfloat16) if t.is_floating_point() else t)(torch.as_tensor(a))

    def _A_setup():
        B, S, D = (1, 2048, 576)
        return {'x': _w((lambda *s: torch.randn(*s, dtype=torch.bfloat16) * 0.05)(B, S, D)), 'wqkv': _w((lambda *s: torch.randn(*s, dtype=torch.bfloat16) * 0.05)(D, 3 * D)), 'wo': _w((lambda *s: torch.randn(*s, dtype=torch.bfloat16) * 0.05)(D, D))}
    _A_in = _A_setup()

    def _B_setup():
        B, S, D, F = (1, 2048, 576, 4608)
        return {'x': _w((lambda *s: torch.randn(*s, dtype=torch.bfloat16) * 0.05)(B, S, D)), 'w1': _w((lambda *s: torch.randn(*s, dtype=torch.bfloat16) * 3.2)(D, F) * D ** (-0.5)), 'w2': _w((lambda *s: torch.randn(*s, dtype=torch.bfloat16) * 0.4)(F, D) * F ** (-0.5))}
    _B_in = _B_setup()
    return {'A_x': _A_in['x'], 'A_wqkv': _A_in['wqkv'], 'A_wo': _A_in['wo'], 'B_x': _B_in['x'], 'B_w1': _B_in['w1'], 'B_w2': _B_in['w2'], 'c': _w((lambda *s: torch.randn(*s, dtype=torch.bfloat16) * 0.1)(1, 576) * 8.0), 'w_mod': _w((lambda *s: torch.randn(*s, dtype=torch.bfloat16) * 0.1)(576, 6 * 576) * 576 ** (-0.5) * 8.0)}

def reference(A_x, A_wqkv, A_wo, B_x, B_w1, B_w2, c, w_mod):

    def _A_ref(x, wqkv, wo):
        B, S, D = x.shape
        H = 32
        Dh = D // H
        qkv = (lambda x, *d: x.permute(*d))((x @ wqkv).reshape(B, S, 3, H, Dh), 2, 0, 3, 1, 4)
        q, k, v = (qkv[0], qkv[1], qkv[2])
        scale = Dh ** (-0.5)
        scores = torch.einsum('bhqd,bhkd->bhqk', q, k) * scale
        p = _softmax(scores, axis=-1)
        o = torch.einsum('bhqk,bhkd->bhqd', p, v)
        return (lambda x, *d: x.permute(*d))(o, 0, 2, 1, 3).reshape(B, S, D) @ wo

    def _B_ref(x, w1, w2):
        h = torch.einsum('bsd,df->bsf', x, w1)
        h = _silu(h)
        out = torch.einsum('bsf,fd->bsd', h, w2)
        return out
    x = A_x
    mod = (_silu(c) @ w_mod).reshape(c.shape[0], 6, 1, -1)
    sa, ca, ga, sb, cb, gb = (mod[:, 0].clone(), mod[:, 1].clone(), mod[:, 2].clone(), mod[:, 3].clone(), mod[:, 4].clone(), mod[:, 5].clone())
    h = _layernorm(x, axis=-1) * (1 + ca) + sa
    x = x + ga * _A_ref(h, A_wqkv, A_wo)
    h = _layernorm(x, axis=-1) * (1 + cb) + sb
    x = x + gb * _B_ref(h, B_w1, B_w2)
    return x
```

```cpp
#include <cuda_runtime.h>
#include <cuda_bf16.h>
#include <cuda.h>
#include <stdint.h>

namespace {

constexpr int SEQ = 2048, DM = 576, DHEAD = 18, FF = 4608;
constexpr int SLOT_BYTES = SEQ * 48;

typedef __nv_bfloat16 bf16;

__device__ __align__(1024) bf16    g_mod[6 * DM];
__device__ __align__(1024) bf16    g_xn[SEQ * DM];
__device__ __align__(1024) uint8_t g_qkvp[96 * SLOT_BYTES];
__device__ __align__(1024) float   g_nrm[16 * 64];
__device__ __align__(1024) bf16    g_o[SEQ * DM];
__device__ __align__(1024) bf16    g_x2[SEQ * DM];
__device__ __align__(1024) bf16    g_h2[SEQ * DM];
__device__ __align__(1024) bf16    g_H[SEQ * FF];
__device__ __align__(1024) float4  g_part[128 * 128 * 288 / 4];
__device__ __align__(1024) float2  g_stats[SEQ * 8];
__device__ unsigned int g_cnt[128];

__device__ __forceinline__ uint32_t s2u(const void* p) { return (uint32_t)__cvta_generic_to_shared(p); }
__device__ __forceinline__ void mbar_init(uint32_t b, uint32_t c) { asm volatile("mbarrier.init.shared::cta.b64 [%0], %1;" :: "r"(b), "r"(c) : "memory"); }
__device__ __forceinline__ void mbar_expect(uint32_t b, uint32_t bytes) { asm volatile("mbarrier.arrive.expect_tx.shared::cta.b64 _, [%0], %1;" :: "r"(b), "r"(bytes) : "memory"); }
__device__ __forceinline__ void mbar_arrive(uint32_t b) { asm volatile("mbarrier.arrive.shared::cta.b64 _, [%0];" :: "r"(b) : "memory"); }
__device__ __forceinline__ bool mbar_try(uint32_t b, uint32_t ph) {
  uint32_t ok;
  asm volatile("{\n.reg .pred p;\nmbarrier.try_wait.parity.shared::cta.b64 p, [%1], %2;\nselp.u32 %0, 1, 0, p;\n}" : "=r"(ok) : "r"(b), "r"(ph) : "memory");
  return ok != 0;
}
__device__ __forceinline__ void mbar_wait(uint32_t b, uint32_t ph) {
  if (!mbar_try(b, ph)) {
    for (int n = 0; n < (1 << 22); n++) if (mbar_try(b, ph)) break;
  }
}
__device__ __forceinline__ void fence_barrier_init() { asm volatile("fence.mbarrier_init.release.cluster;" ::: "memory"); }
__device__ __forceinline__ void fence_async_smem() { asm volatile("fence.proxy.async.shared::cta;" ::: "memory"); }
__device__ __forceinline__ void bar_sync(int id, int n) { asm volatile("bar.sync %0, %1;" :: "r"(id), "r"(n) : "memory"); }
__device__ __forceinline__ void pdl_wait() { asm volatile("griddepcontrol.wait;" ::: "memory"); }
__device__ __forceinline__ void pdl_launch() { asm volatile("griddepcontrol.launch_dependents;" ::: "memory"); }
__device__ __forceinline__ void bulk_g2s(uint32_t dst, const void* src, uint32_t bytes, uint32_t bar) {
  asm volatile("cp.async.bulk.shared::cluster.global.mbarrier::complete_tx::bytes [%0], [%1], %2, [%3];" :: "r"(dst), "l"(src), "r"(bytes), "r"(bar) : "memory");
}
__device__ __forceinline__ void bulk_s2g(void* dst, uint32_t src, uint32_t bytes) {
  asm volatile("cp.async.bulk.global.shared::cta.bulk_group [%0], [%1], %2;" :: "l"(dst), "r"(src), "r"(bytes) : "memory");
}
__device__ __forceinline__ void bulk_commit() { asm volatile("cp.async.bulk.commit_group;" ::: "memory"); }
__device__ __forceinline__ void bulk_wait_all() { asm volatile("cp.async.bulk.wait_group 0;" ::: "memory"); }
__device__ __forceinline__ void tma2d(uint32_t dst, const CUtensorMap* m, int x, int y, uint32_t bar) {
  asm volatile("cp.async.bulk.tensor.2d.shared::cluster.global.mbarrier::complete_tx::bytes [%0], [%1, {%3, %4}], [%2];"
               :: "r"(dst), "l"(m), "r"(bar), "r"(x), "r"(y) : "memory");
}
__device__ __forceinline__ void tma5d(uint32_t dst, const CUtensorMap* m, int c0, int c1, int c2, int c3, int c4, uint32_t bar) {
  asm volatile("cp.async.bulk.tensor.5d.shared::cluster.global.mbarrier::complete_tx::bytes [%0], [%1, {%3, %4, %5, %6, %7}], [%2];"
               :: "r"(dst), "l"(m), "r"(bar), "r"(c0), "r"(c1), "r"(c2), "r"(c3), "r"(c4) : "memory");
}
__device__ __forceinline__ void tmap_prefetch(const CUtensorMap* m) { asm volatile("prefetch.tensormap [%0];" :: "l"(m) : "memory"); }
__device__ __forceinline__ void wg_fence() { asm volatile("wgmma.fence.sync.aligned;" ::: "memory"); }
__device__ __forceinline__ void wg_commit() { asm volatile("wgmma.commit_group.sync.aligned;" ::: "memory"); }
template <int N> __device__ __forceinline__ void wg_wait() { asm volatile("wgmma.wait_group.sync.aligned %0;" :: "n"(N) : "memory"); }
__device__ __forceinline__ uint64_t mkdesc(uint32_t addr, uint32_t lbo, uint32_t sbo, int sw) {
  return (uint64_t)((addr & 0x3FFFF) >> 4) | ((uint64_t)(lbo >> 4) << 16) | ((uint64_t)(sbo >> 4) << 32) | ((uint64_t)sw << 62);
}
template <int N> __device__ __forceinline__ void fence_regs(float (&d)[N]) {
#pragma unroll
  for (int i = 0; i < N; i++) asm volatile("" : "+f"(d[i]) :: "memory");
}
template <int N> __device__ __forceinline__ void fence_regs(uint32_t (&d)[N]) {
#pragma unroll
  for (int i = 0; i < N; i++) asm volatile("" : "+r"(d[i]) :: "memory");
}
__device__ __forceinline__ float ex2(float x) { float y; asm("ex2.approx.ftz.f32 %0, %1;" : "=f"(y) : "f"(x)); return y; }
__device__ __forceinline__ float tanh_fast(float x) { float y; asm("tanh.approx.f32 %0, %1;" : "=f"(y) : "f"(x)); return y; }
__device__ __forceinline__ uint32_t pack_bf16(float lo, float hi) { uint32_t v; asm("cvt.rn.bf16x2.f32 %0, %1, %2;" : "=r"(v) : "f"(hi), "f"(lo)); return v; }
__device__ __forceinline__ float bf_lo(uint32_t v) { return __uint_as_float(v << 16); }
__device__ __forceinline__ float bf_hi(uint32_t v) { return __uint_as_float(v & 0xFFFF0000u); }
__device__ __forceinline__ float bf_round(float x) { return __bfloat162float(__float2bfloat16_rn(x)); }
__device__ __forceinline__ uint32_t hfma2(uint32_t a, uint32_t b, uint32_t c) { uint32_t d; asm("fma.rn.bf16x2 %0, %1, %2, %3;" : "=r"(d) : "r"(a), "r"(b), "r"(c)); return d; }
__device__ __forceinline__ uint32_t hadd2(uint32_t a, uint32_t b) { uint32_t d; asm("add.rn.bf16x2 %0, %1, %2;" : "=r"(d) : "r"(a), "r"(b)); return d; }
__device__ __forceinline__ uint4 lds128(uint32_t a) { uint4 v; asm volatile("ld.shared.v4.b32 {%0,%1,%2,%3}, [%4];" : "=r"(v.x), "=r"(v.y), "=r"(v.z), "=r"(v.w) : "r"(a)); return v; }
__device__ __forceinline__ void sts128(uint32_t a, uint4 v) { asm volatile("st.shared.v4.b32 [%0], {%1,%2,%3,%4};" :: "r"(a), "r"(v.x), "r"(v.y), "r"(v.z), "r"(v.w) : "memory"); }
__device__ __forceinline__ uint32_t lds32(uint32_t a) { uint32_t v; asm volatile("ld.shared.b32 %0, [%1];" : "=r"(v) : "r"(a)); return v; }
__device__ __forceinline__ void sts32(uint32_t a, uint32_t v) { asm volatile("st.shared.b32 [%0], %1;" :: "r"(a), "r"(v) : "memory"); }
template <int R> __device__ __forceinline__ void reg_inc() { asm volatile("setmaxnreg.inc.sync.aligned.u32 %0;" :: "n"(R)); }
template <int R> __device__ __forceinline__ void reg_dec() { asm volatile("setmaxnreg.dec.sync.aligned.u32 %0;" :: "n"(R)); }

__device__ __forceinline__ void epoch_barrier(unsigned int* cnt, unsigned int n) {
  unsigned int old;
  asm volatile("atom.add.release.gpu.global.u32 %0, [%1], 1;" : "=r"(old) : "l"(cnt) : "memory");
  const unsigned int target = (old / n + 1) * n;
  for (int it = 0;; it++) {
    unsigned int v;
    asm volatile("ld.acquire.gpu.global.u32 %0, [%1];" : "=r"(v) : "l"(cnt) : "memory");
    if ((int)(v - target) >= 0 || it > (1 << 22)) break;
  }
}

#define TL(k, i)
#define TLT(k, i, t)

__device__ __forceinline__ void wgmma_ss_n216_tb(float (&d)[108], uint64_t da, uint64_t db, int sd) {
  asm volatile("{\n.reg .pred p;\nsetp.ne.b32 p, %110, 0;\n"
    "wgmma.mma_async.sync.aligned.m64n216k16.f32.bf16.bf16 "
    "{%0, %1, %2, %3, %4, %5, %6, %7, %8, %9, %10, %11, %12, %13, %14, %15, %16, %17, %18, %19, %20, %21, %22, %23, %24, %25, %26, %27, %28, %29, %30, %31, %32, %33, %34, %35, %36, %37, %38, %39, %40, %41, %42, %43, %44, %45, %46, %47, %48, %49, %50, %51, %52, %53, %54, %55, %56, %57, %58, %59, %60, %61, %62, %63, %64, %65, %66, %67, %68, %69, %70, %71, %72, %73, %74, %75, %76, %77, %78, %79, %80, %81, %82, %83, %84, %85, %86, %87, %88, %89, %90, %91, %92, %93, %94, %95, %96, %97, %98, %99, %100, %101, %102, %103, %104, %105, %106, %107}, %108, %109, p, 1, 1, 0, 1;\n}\n"
    : "+f"(d[0]), "+f"(d[1]), "+f"(d[2]), "+f"(d[3]), "+f"(d[4]), "+f"(d[5]), "+f"(d[6]), "+f"(d[7]), "+f"(d[8]), "+f"(d[9]), "+f"(d[10]), "+f"(d[11]), "+f"(d[12]), "+f"(d[13]), "+f"(d[14]), "+f"(d[15]), "+f"(d[16]), "+f"(d[17]), "+f"(d[18]), "+f"(d[19]), "+f"(d[20]), "+f"(d[21]), "+f"(d[22]), "+f"(d[23]), "+f"(d[24]), "+f"(d[25]), "+f"(d[26]), "+f"(d[27]), "+f"(d[28]), "+f"(d[29]), "+f"(d[30]), "+f"(d[31]), "+f"(d[32]), "+f"(d[33]), "+f"(d[34]), "+f"(d[35]), "+f"(d[36]), "+f"(d[37]), "+f"(d[38]), "+f"(d[39]), "+f"(d[40]), "+f"(d[41]), "+f"(d[42]), "+f"(d[43]), "+f"(d[44]), "+f"(d[45]), "+f"(d[46]), "+f"(d[47]), "+f"(d[48]), "+f"(d[49]), "+f"(d[50]), "+f"(d[51]), "+f"(d[52]), "+f"(d[53]), "+f"(d[54]), "+f"(d[55]), "+f"(d[56]), "+f"(d[57]), "+f"(d[58]), "+f"(d[59]), "+f"(d[60]), "+f"(d[61]), "+f"(d[62]), "+f"(d[63]), "+f"(d[64]), "+f"(d[65]), "+f"(d[66]), "+f"(d[67]), "+f"(d[68]), "+f"(d[69]), "+f"(d[70]), "+f"(d[71]), "+f"(d[72]), "+f"(d[73]), "+f"(d[74]), "+f"(d[75]), "+f"(d[76]), "+f"(d[77]), "+f"(d[78]), "+f"(d[79]), "+f"(d[80]), "+f"(d[81]), "+f"(d[82]), "+f"(d[83]), "+f"(d[84]), "+f"(d[85]), "+f"(d[86]), "+f"(d[87]), "+f"(d[88]), "+f"(d[89]), "+f"(d[90]), "+f"(d[91]), "+f"(d[92]), "+f"(d[93]), "+f"(d[94]), "+f"(d[95]), "+f"(d[96]), "+f"(d[97]), "+f"(d[98]), "+f"(d[99]), "+f"(d[100]), "+f"(d[101]), "+f"(d[102]), "+f"(d[103]), "+f"(d[104]), "+f"(d[105]), "+f"(d[106]), "+f"(d[107])
    : "l"(da), "l"(db), "r"(sd));
}
__device__ __forceinline__ void wgmma_ss_n72_tb(float (&d)[36], uint64_t da, uint64_t db, int sd) {
  asm volatile("{\n.reg .pred p;\nsetp.ne.b32 p, %38, 0;\n"
    "wgmma.mma_async.sync.aligned.m64n72k16.f32.bf16.bf16 "
    "{%0, %1, %2, %3, %4, %5, %6, %7, %8, %9, %10, %11, %12, %13, %14, %15, %16, %17, %18, %19, %20, %21, %22, %23, %24, %25, %26, %27, %28, %29, %30, %31, %32, %33, %34, %35}, %36, %37, p, 1, 1, 0, 1;\n}\n"
    : "+f"(d[0]), "+f"(d[1]), "+f"(d[2]), "+f"(d[3]), "+f"(d[4]), "+f"(d[5]), "+f"(d[6]), "+f"(d[7]), "+f"(d[8]), "+f"(d[9]), "+f"(d[10]), "+f"(d[11]), "+f"(d[12]), "+f"(d[13]), "+f"(d[14]), "+f"(d[15]), "+f"(d[16]), "+f"(d[17]), "+f"(d[18]), "+f"(d[19]), "+f"(d[20]), "+f"(d[21]), "+f"(d[22]), "+f"(d[23]), "+f"(d[24]), "+f"(d[25]), "+f"(d[26]), "+f"(d[27]), "+f"(d[28]), "+f"(d[29]), "+f"(d[30]), "+f"(d[31]), "+f"(d[32]), "+f"(d[33]), "+f"(d[34]), "+f"(d[35])
    : "l"(da), "l"(db), "r"(sd));
}
__device__ __forceinline__ void wgmma_ss_n192_tb(float (&d)[96], uint64_t da, uint64_t db, int sd) {
  asm volatile("{\n.reg .pred p;\nsetp.ne.b32 p, %98, 0;\n"
    "wgmma.mma_async.sync.aligned.m64n192k16.f32.bf16.bf16 "
    "{%0, %1, %2, %3, %4, %5, %6, %7, %8, %9, %10, %11, %12, %13, %14, %15, %16, %17, %18, %19, %20, %21, %22, %23, %24, %25, %26, %27, %28, %29, %30, %31, %32, %33, %34, %35, %36, %37, %38, %39, %40, %41, %42, %43, %44, %45, %46, %47, %48, %49, %50, %51, %52, %53, %54, %55, %56, %57, %58, %59, %60, %61, %62, %63, %64, %65, %66, %67, %68, %69, %70, %71, %72, %73, %74, %75, %76, %77, %78, %79, %80, %81, %82, %83, %84, %85, %86, %87, %88, %89, %90, %91, %92, %93, %94, %95}, %96, %97, p, 1, 1, 0, 1;\n}\n"
    : "+f"(d[0]), "+f"(d[1]), "+f"(d[2]), "+f"(d[3]), "+f"(d[4]), "+f"(d[5]), "+f"(d[6]), "+f"(d[7]), "+f"(d[8]), "+f"(d[9]), "+f"(d[10]), "+f"(d[11]), "+f"(d[12]), "+f"(d[13]), "+f"(d[14]), "+f"(d[15]), "+f"(d[16]), "+f"(d[17]), "+f"(d[18]), "+f"(d[19]), "+f"(d[20]), "+f"(d[21]), "+f"(d[22]), "+f"(d[23]), "+f"(d[24]), "+f"(d[25]), "+f"(d[26]), "+f"(d[27]), "+f"(d[28]), "+f"(d[29]), "+f"(d[30]), "+f"(d[31]), "+f"(d[32]), "+f"(d[33]), "+f"(d[34]), "+f"(d[35]), "+f"(d[36]), "+f"(d[37]), "+f"(d[38]), "+f"(d[39]), "+f"(d[40]), "+f"(d[41]), "+f"(d[42]), "+f"(d[43]), "+f"(d[44]), "+f"(d[45]), "+f"(d[46]), "+f"(d[47]), "+f"(d[48]), "+f"(d[49]), "+f"(d[50]), "+f"(d[51]), "+f"(d[52]), "+f"(d[53]), "+f"(d[54]), "+f"(d[55]), "+f"(d[56]), "+f"(d[57]), "+f"(d[58]), "+f"(d[59]), "+f"(d[60]), "+f"(d[61]), "+f"(d[62]), "+f"(d[63]), "+f"(d[64]), "+f"(d[65]), "+f"(d[66]), "+f"(d[67]), "+f"(d[68]), "+f"(d[69]), "+f"(d[70]), "+f"(d[71]), "+f"(d[72]), "+f"(d[73]), "+f"(d[74]), "+f"(d[75]), "+f"(d[76]), "+f"(d[77]), "+f"(d[78]), "+f"(d[79]), "+f"(d[80]), "+f"(d[81]), "+f"(d[82]), "+f"(d[83]), "+f"(d[84]), "+f"(d[85]), "+f"(d[86]), "+f"(d[87]), "+f"(d[88]), "+f"(d[89]), "+f"(d[90]), "+f"(d[91]), "+f"(d[92]), "+f"(d[93]), "+f"(d[94]), "+f"(d[95])
    : "l"(da), "l"(db), "r"(sd));
}
__device__ __forceinline__ void wgmma_ss0_n192_tb(float (&d)[96], uint64_t da, uint64_t db) {
  asm volatile("{\n.reg .pred p;\nsetp.ne.b32 p, 0, 0;\n"
    "wgmma.mma_async.sync.aligned.m64n192k16.f32.bf16.bf16 "
    "{%0, %1, %2, %3, %4, %5, %6, %7, %8, %9, %10, %11, %12, %13, %14, %15, %16, %17, %18, %19, %20, %21, %22, %23, %24, %25, %26, %27, %28, %29, %30, %31, %32, %33, %34, %35, %36, %37, %38, %39, %40, %41, %42, %43, %44, %45, %46, %47, %48, %49, %50, %51, %52, %53, %54, %55, %56, %57, %58, %59, %60, %61, %62, %63, %64, %65, %66, %67, %68, %69, %70, %71, %72, %73, %74, %75, %76, %77, %78, %79, %80, %81, %82, %83, %84, %85, %86, %87, %88, %89, %90, %91, %92, %93, %94, %95}, %96, %97, p, 1, 1, 0, 1;\n}\n"
    : "=f"(d[0]), "=f"(d[1]), "=f"(d[2]), "=f"(d[3]), "=f"(d[4]), "=f"(d[5]), "=f"(d[6]), "=f"(d[7]), "=f"(d[8]), "=f"(d[9]), "=f"(d[10]), "=f"(d[11]), "=f"(d[12]), "=f"(d[13]), "=f"(d[14]), "=f"(d[15]), "=f"(d[16]), "=f"(d[17]), "=f"(d[18]), "=f"(d[19]), "=f"(d[20]), "=f"(d[21]), "=f"(d[22]), "=f"(d[23]), "=f"(d[24]), "=f"(d[25]), "=f"(d[26]), "=f"(d[27]), "=f"(d[28]), "=f"(d[29]), "=f"(d[30]), "=f"(d[31]), "=f"(d[32]), "=f"(d[33]), "=f"(d[34]), "=f"(d[35]), "=f"(d[36]), "=f"(d[37]), "=f"(d[38]), "=f"(d[39]), "=f"(d[40]), "=f"(d[41]), "=f"(d[42]), "=f"(d[43]), "=f"(d[44]), "=f"(d[45]), "=f"(d[46]), "=f"(d[47]), "=f"(d[48]), "=f"(d[49]), "=f"(d[50]), "=f"(d[51]), "=f"(d[52]), "=f"(d[53]), "=f"(d[54]), "=f"(d[55]), "=f"(d[56]), "=f"(d[57]), "=f"(d[58]), "=f"(d[59]), "=f"(d[60]), "=f"(d[61]), "=f"(d[62]), "=f"(d[63]), "=f"(d[64]), "=f"(d[65]), "=f"(d[66]), "=f"(d[67]), "=f"(d[68]), "=f"(d[69]), "=f"(d[70]), "=f"(d[71]), "=f"(d[72]), "=f"(d[73]), "=f"(d[74]), "=f"(d[75]), "=f"(d[76]), "=f"(d[77]), "=f"(d[78]), "=f"(d[79]), "=f"(d[80]), "=f"(d[81]), "=f"(d[82]), "=f"(d[83]), "=f"(d[84]), "=f"(d[85]), "=f"(d[86]), "=f"(d[87]), "=f"(d[88]), "=f"(d[89]), "=f"(d[90]), "=f"(d[91]), "=f"(d[92]), "=f"(d[93]), "=f"(d[94]), "=f"(d[95])
    : "l"(da), "l"(db));
}
__device__ __forceinline__ void wgmma_ss_n160_tb(float (&d)[80], uint64_t da, uint64_t db, int sd) {
  asm volatile("{\n.reg .pred p;\nsetp.ne.b32 p, %82, 0;\n"
    "wgmma.mma_async.sync.aligned.m64n160k16.f32.bf16.bf16 "
    "{%0, %1, %2, %3, %4, %5, %6, %7, %8, %9, %10, %11, %12, %13, %14, %15, %16, %17, %18, %19, %20, %21, %22, %23, %24, %25, %26, %27, %28, %29, %30, %31, %32, %33, %34, %35, %36, %37, %38, %39, %40, %41, %42, %43, %44, %45, %46, %47, %48, %49, %50, %51, %52, %53, %54, %55, %56, %57, %58, %59, %60, %61, %62, %63, %64, %65, %66, %67, %68, %69, %70, %71, %72, %73, %74, %75, %76, %77, %78, %79}, %80, %81, p, 1, 1, 0, 1;\n}\n"
    : "+f"(d[0]), "+f"(d[1]), "+f"(d[2]), "+f"(d[3]), "+f"(d[4]), "+f"(d[5]), "+f"(d[6]), "+f"(d[7]), "+f"(d[8]), "+f"(d[9]), "+f"(d[10]), "+f"(d[11]), "+f"(d[12]), "+f"(d[13]), "+f"(d[14]), "+f"(d[15]), "+f"(d[16]), "+f"(d[17]), "+f"(d[18]), "+f"(d[19]), "+f"(d[20]), "+f"(d[21]), "+f"(d[22]), "+f"(d[23]), "+f"(d[24]), "+f"(d[25]), "+f"(d[26]), "+f"(d[27]), "+f"(d[28]), "+f"(d[29]), "+f"(d[30]), "+f"(d[31]), "+f"(d[32]), "+f"(d[33]), "+f"(d[34]), "+f"(d[35]), "+f"(d[36]), "+f"(d[37]), "+f"(d[38]), "+f"(d[39]), "+f"(d[40]), "+f"(d[41]), "+f"(d[42]), "+f"(d[43]), "+f"(d[44]), "+f"(d[45]), "+f"(d[46]), "+f"(d[47]), "+f"(d[48]), "+f"(d[49]), "+f"(d[50]), "+f"(d[51]), "+f"(d[52]), "+f"(d[53]), "+f"(d[54]), "+f"(d[55]), "+f"(d[56]), "+f"(d[57]), "+f"(d[58]), "+f"(d[59]), "+f"(d[60]), "+f"(d[61]), "+f"(d[62]), "+f"(d[63]), "+f"(d[64]), "+f"(d[65]), "+f"(d[66]), "+f"(d[67]), "+f"(d[68]), "+f"(d[69]), "+f"(d[70]), "+f"(d[71]), "+f"(d[72]), "+f"(d[73]), "+f"(d[74]), "+f"(d[75]), "+f"(d[76]), "+f"(d[77]), "+f"(d[78]), "+f"(d[79])
    : "l"(da), "l"(db), "r"(sd));
}
__device__ __forceinline__ void wgmma_ss_n128_tb(float (&d)[64], uint64_t da, uint64_t db, int sd) {
  asm volatile("{\n.reg .pred p;\nsetp.ne.b32 p, %66, 0;\n"
    "wgmma.mma_async.sync.aligned.m64n128k16.f32.bf16.bf16 "
    "{%0, %1, %2, %3, %4, %5, %6, %7, %8, %9, %10, %11, %12, %13, %14, %15, %16, %17, %18, %19, %20, %21, %22, %23, %24, %25, %26, %27, %28, %29, %30, %31, %32, %33, %34, %35, %36, %37, %38, %39, %40, %41, %42, %43, %44, %45, %46, %47, %48, %49, %50, %51, %52, %53, %54, %55, %56, %57, %58, %59, %60, %61, %62, %63}, %64, %65, p, 1, 1, 0, 1;\n}\n"
    : "+f"(d[0]), "+f"(d[1]), "+f"(d[2]), "+f"(d[3]), "+f"(d[4]), "+f"(d[5]), "+f"(d[6]), "+f"(d[7]), "+f"(d[8]), "+f"(d[9]), "+f"(d[10]), "+f"(d[11]), "+f"(d[12]), "+f"(d[13]), "+f"(d[14]), "+f"(d[15]), "+f"(d[16]), "+f"(d[17]), "+f"(d[18]), "+f"(d[19]), "+f"(d[20]), "+f"(d[21]), "+f"(d[22]), "+f"(d[23]), "+f"(d[24]), "+f"(d[25]), "+f"(d[26]), "+f"(d[27]), "+f"(d[28]), "+f"(d[29]), "+f"(d[30]), "+f"(d[31]), "+f"(d[32]), "+f"(d[33]), "+f"(d[34]), "+f"(d[35]), "+f"(d[36]), "+f"(d[37]), "+f"(d[38]), "+f"(d[39]), "+f"(d[40]), "+f"(d[41]), "+f"(d[42]), "+f"(d[43]), "+f"(d[44]), "+f"(d[45]), "+f"(d[46]), "+f"(d[47]), "+f"(d[48]), "+f"(d[49]), "+f"(d[50]), "+f"(d[51]), "+f"(d[52]), "+f"(d[53]), "+f"(d[54]), "+f"(d[55]), "+f"(d[56]), "+f"(d[57]), "+f"(d[58]), "+f"(d[59]), "+f"(d[60]), "+f"(d[61]), "+f"(d[62]), "+f"(d[63])
    : "l"(da), "l"(db), "r"(sd));
}
__device__ __forceinline__ void wgmma_rs_n64(float (&d)[32], uint32_t a0, uint32_t a1, uint32_t a2, uint32_t a3, uint64_t db, int sd) {
  asm volatile("{\n.reg .pred p;\nsetp.ne.b32 p, %37, 0;\n"
    "wgmma.mma_async.sync.aligned.m64n64k16.f32.bf16.bf16 "
    "{%0, %1, %2, %3, %4, %5, %6, %7, %8, %9, %10, %11, %12, %13, %14, %15, %16, %17, %18, %19, %20, %21, %22, %23, %24, %25, %26, %27, %28, %29, %30, %31}, {%32,%33,%34,%35}, %36, p, 1, 1, 0;\n}\n"
    : "+f"(d[0]), "+f"(d[1]), "+f"(d[2]), "+f"(d[3]), "+f"(d[4]), "+f"(d[5]), "+f"(d[6]), "+f"(d[7]), "+f"(d[8]), "+f"(d[9]), "+f"(d[10]), "+f"(d[11]), "+f"(d[12]), "+f"(d[13]), "+f"(d[14]), "+f"(d[15]), "+f"(d[16]), "+f"(d[17]), "+f"(d[18]), "+f"(d[19]), "+f"(d[20]), "+f"(d[21]), "+f"(d[22]), "+f"(d[23]), "+f"(d[24]), "+f"(d[25]), "+f"(d[26]), "+f"(d[27]), "+f"(d[28]), "+f"(d[29]), "+f"(d[30]), "+f"(d[31])
    : "r"(a0), "r"(a1), "r"(a2), "r"(a3), "l"(db), "r"(sd));
}
__device__ __forceinline__ void wgmma_rs0_n64(float (&d)[32], uint32_t a0, uint32_t a1, uint32_t a2, uint32_t a3, uint64_t db) {
  asm volatile("{\n.reg .pred p;\nsetp.ne.b32 p, 0, 0;\n"
    "wgmma.mma_async.sync.aligned.m64n64k16.f32.bf16.bf16 "
    "{%0, %1, %2, %3, %4, %5, %6, %7, %8, %9, %10, %11, %12, %13, %14, %15, %16, %17, %18, %19, %20, %21, %22, %23, %24, %25, %26, %27, %28, %29, %30, %31}, {%32,%33,%34,%35}, %36, p, 1, 1, 0;\n}\n"
    : "=f"(d[0]), "=f"(d[1]), "=f"(d[2]), "=f"(d[3]), "=f"(d[4]), "=f"(d[5]), "=f"(d[6]), "=f"(d[7]), "=f"(d[8]), "=f"(d[9]), "=f"(d[10]), "=f"(d[11]), "=f"(d[12]), "=f"(d[13]), "=f"(d[14]), "=f"(d[15]), "=f"(d[16]), "=f"(d[17]), "=f"(d[18]), "=f"(d[19]), "=f"(d[20]), "=f"(d[21]), "=f"(d[22]), "=f"(d[23]), "=f"(d[24]), "=f"(d[25]), "=f"(d[26]), "=f"(d[27]), "=f"(d[28]), "=f"(d[29]), "=f"(d[30]), "=f"(d[31])
    : "r"(a0), "r"(a1), "r"(a2), "r"(a3), "l"(db));
}
__device__ __forceinline__ void wgmma_rs_n24_tb(float (&d)[12], uint32_t a0, uint32_t a1, uint32_t a2, uint32_t a3, uint64_t db, int sd) {
  asm volatile("{\n.reg .pred p;\nsetp.ne.b32 p, %17, 0;\n"
    "wgmma.mma_async.sync.aligned.m64n24k16.f32.bf16.bf16 "
    "{%0, %1, %2, %3, %4, %5, %6, %7, %8, %9, %10, %11}, {%12,%13,%14,%15}, %16, p, 1, 1, 1;\n}\n"
    : "+f"(d[0]), "+f"(d[1]), "+f"(d[2]), "+f"(d[3]), "+f"(d[4]), "+f"(d[5]), "+f"(d[6]), "+f"(d[7]), "+f"(d[8]), "+f"(d[9]), "+f"(d[10]), "+f"(d[11])
    : "r"(a0), "r"(a1), "r"(a2), "r"(a3), "l"(db), "r"(sd));
}

__global__ void __launch_bounds__(256) k0_mod_ln(const bf16* __restrict__ x, const bf16* __restrict__ c, const bf16* __restrict__ wmod) {
  __shared__ float red[8][32];
  TL(0, 0);
  pdl_launch();
  const int t = threadIdx.x, warp = t >> 5, lane = t & 31, b = blockIdx.x;
  const int r0 = b * 16 + warp * 2;
  const uint32_t* xr = reinterpret_cast<const uint32_t*>(x + (size_t)r0 * DM);
  uint32_t xv[2][9];
#pragma unroll
  for (int j = 0; j < 9; j++) { xv[0][j] = __ldg(xr + lane + 32 * j); xv[1][j] = __ldg(xr + 288 + lane + 32 * j); }
  uint4 wv[9]; float cs[9];
  const bool do_mod = b < 108;
  const int cq = t & 3, kr = t >> 2;
  if (do_mod) {
#pragma unroll
    for (int j = 0; j < 9; j++) {
      const int k = kr + 64 * j;
      wv[j] = __ldg(reinterpret_cast<const uint4*>(wmod + (size_t)k * (6 * DM) + b * 32 + cq * 8));
      cs[j] = __bfloat162float(c[k]);
    }
  }
#pragma unroll
  for (int r = 0; r < 2; r++) {
    float s = 0.f;
#pragma unroll
    for (int j = 0; j < 9; j++) s += bf_lo(xv[r][j]) + bf_hi(xv[r][j]);
#pragma unroll
    for (int o = 16; o; o >>= 1) s += __shfl_xor_sync(0xffffffffu, s, o);
    const float m = s * (1.0f / DM);
    float v = 0.f;
#pragma unroll
    for (int j = 0; j < 9; j++) { const float a = bf_lo(xv[r][j]) - m, d = bf_hi(xv[r][j]) - m; v = fmaf(a, a, v); v = fmaf(d, d, v); }
#pragma unroll
    for (int o = 16; o; o >>= 1) v += __shfl_xor_sync(0xffffffffu, v, o);
    const float rs = 1.0f / sqrtf(v * (1.0f / DM) + 1e-5f);
    uint32_t* o32 = reinterpret_cast<uint32_t*>(g_xn + (size_t)(r0 + r) * DM);
#pragma unroll
    for (int j = 0; j < 9; j++) o32[lane + 32 * j] = pack_bf16((bf_lo(xv[r][j]) - m) * rs, (bf_hi(xv[r][j]) - m) * rs);
  }
  if (do_mod) {
    float acc[8];
#pragma unroll
    for (int i = 0; i < 8; i++) acc[i] = 0.f;
#pragma unroll
    for (int j = 0; j < 9; j++) {
      const float s = bf_round(cs[j] / (1.0f + __expf(-cs[j])));
      const uint32_t w[4] = {wv[j].x, wv[j].y, wv[j].z, wv[j].w};
#pragma unroll
      for (int i = 0; i < 4; i++) { acc[2 * i] = fmaf(s, bf_lo(w[i]), acc[2 * i]); acc[2 * i + 1] = fmaf(s, bf_hi(w[i]), acc[2 * i + 1]); }
    }
#pragma unroll
    for (int i = 0; i < 8; i++) {
#pragma unroll
      for (int o = 4; o < 32; o <<= 1) acc[i] += __shfl_xor_sync(0xffffffffu, acc[i], o);
    }
    if (lane < 4) {
#pragma unroll
      for (int i = 0; i < 8; i++) red[warp][lane * 8 + i] = acc[i];
    }
    __syncthreads();
    if (t < 32) {
      float s = 0.f;
#pragma unroll
      for (int w = 0; w < 8; w++) s += red[w][t];
      g_mod[b * 32 + t] = __float2bfloat16_rn(s);
    }
  }
  TL(0, 3);
}

constexpr int K1_NST = 5;
constexpr int K1_A = 0, K1_W = 147456, K1_MOD = K1_W + K1_NST * 16384, K1_RED = K1_MOD + 2304, K1_BAR = K1_RED + 256;
constexpr int K1_SMEM = K1_BAR + 8 * (9 + 2 * K1_NST);
#define QSCALE (0.23570226039551584f * 1.4426950408889634f)
__host__ __device__ constexpr bool poly_block(int b) {
  return b == 1 || b == 3 || b == 4 || b == 6 || b == 7;
}
constexpr uint32_t KPAD_POLY = 0x42FE47C0u;
constexpr uint32_t VPAD_ONE  = 0x00003F80u;

__global__ void __launch_bounds__(288, 1) k1_qkv(const __grid_constant__ CUtensorMap tm_xn, const __grid_constant__ CUtensorMap tm_w) {
  extern __shared__ __align__(1024) uint8_t smem[];
  const uint32_t sb = s2u(smem);
  const int tid = threadIdx.x, nt = blockIdx.x & 7, rb = blockIdx.x >> 3;
  const uint32_t bx = sb + K1_BAR, bwf = bx + 72, bwe = bwf + 8 * K1_NST;
  TL(1, 0);
  if (tid == 256) {
    for (int i = 0; i < 9; i++) mbar_init(bx + 8 * i, 1);
    for (int i = 0; i < K1_NST; i++) { mbar_init(bwf + 8 * i, 1); mbar_init(bwe + 8 * i, 2); }
    fence_barrier_init();
    tmap_prefetch(&tm_xn); tmap_prefetch(&tm_w);
  }
  __syncthreads();
  pdl_launch();
  if (tid >= 256) {
    if (tid == 256) {
      for (int st = 0; st < K1_NST; st++) {
        mbar_expect(bwf + 8 * st, 16384);
        for (int g = 0; g < 4; g++) tma2d(sb + K1_W + st * 16384 + g * 4096, &tm_w, nt * 216 + g * 64, st * 32, bwf + 8 * st);
      }
      pdl_wait();
      for (int c = 0; c < 9; c++) { mbar_expect(bx + 8 * c, 16384); tma2d(sb + K1_A + c * 16384, &tm_xn, c * 64, rb * 128, bx + 8 * c); }
      for (int st = K1_NST; st < 18; st++) {
        const int s = st % K1_NST;
        mbar_wait(bwe + 8 * s, (st / K1_NST - 1) & 1);
        mbar_expect(bwf + 8 * s, 16384);
        for (int g = 0; g < 4; g++) tma2d(sb + K1_W + s * 16384 + g * 4096, &tm_w, nt * 216 + g * 64, st * 32, bwf + 8 * s);
      }
    }
    return;
  }
  const int wg = __shfl_sync(0xffffffffu, tid >> 7, 0), wtid = tid & 127, warp = (tid >> 5) & 3, lane = tid & 31, g = lane >> 2, q4 = lane & 3;
  pdl_wait();
  TL(1, 1);
  {
    const uint32_t* m32 = reinterpret_cast<const uint32_t*>(g_mod);
    for (int i = tid; i < 288; i += 256) {
      sts32(sb + K1_MOD + 4 * i, hadd2(m32[288 + i], 0x3F803F80u));
      sts32(sb + K1_MOD + 1152 + 4 * i, m32[i]);
    }
  }
  bar_sync(1, 256);
  auto modulate = [&](int c) {
    mbar_wait(bx + 8 * c, 0);
    const int cg = wtid & 7, r = wg * 64 + (wtid >> 3);
    const uint4 sc = lds128(sb + K1_MOD + c * 128 + cg * 16), sh = lds128(sb + K1_MOD + 1152 + c * 128 + cg * 16);
    const uint32_t a = sb + K1_A + c * 16384 + r * 128 + ((cg ^ (r & 7)) << 4);
#pragma unroll
    for (int i = 0; i < 4; i++) {
      uint4 v = lds128(a + i * 2048);
      v.x = hfma2(v.x, sc.x, sh.x); v.y = hfma2(v.y, sc.y, sh.y); v.z = hfma2(v.z, sc.z, sh.z); v.w = hfma2(v.w, sc.w, sh.w);
      sts128(a + i * 2048, v);
    }
    fence_async_smem();
  };
  float acc[108];
  modulate(0);
  bar_sync(2 + wg, 128);
  const uint64_t da0 = mkdesc(sb + K1_A + wg * 8192, 16, 1024, 1);
  const uint64_t db0 = mkdesc(sb + K1_W, 4096, 1024, 1);
#pragma unroll 1
  for (int c = 0; c < 9; c++) {
#pragma unroll
    for (int h = 0; h < 2; h++) {
      const int st = 2 * c + h, s = st % K1_NST;
      mbar_wait(bwf + 8 * s, (st / K1_NST) & 1);
      wg_fence();
#pragma unroll
      for (int j = 0; j < 2; j++)
        wgmma_ss_n216_tb(acc, da0 + (uint64_t)(c * 1024 + (h * 2 + j) * 2), db0 + (uint64_t)(s * 1024 + j * 128), (st | j) != 0);
      wg_commit();
      if (h == 0 && c < 8) modulate(c + 1);
      if (st > 0) { wg_wait<1>(); if (wtid == 0) mbar_arrive(bwe + 8 * ((st - 1) % K1_NST)); }
    }
    if (c < 8) bar_sync(2 + wg, 128);
  }
  wg_wait<0>();
  fence_regs(acc);
  TL(1, 2);
  bar_sync(1, 256);
  {
    const int tok = wg * 64 + warp * 16 + g;
    const uint32_t base = sb + (tok >> 3) * 384 + (tok & 7) * 16;
    int d = 2 * q4, sl = 0;
#pragma unroll
    for (int i = 0; i < 27; i++) {
      const float sc = (nt * 12 + sl < 32) ? QSCALE : 1.0f;
      const uint32_t a = base + sl * 6144 + (d >> 3) * 128 + (d & 7) * 2;
      sts32(a, pack_bf16(acc[4 * i] * sc, acc[4 * i + 1] * sc));
      sts32(a + 384, pack_bf16(acc[4 * i + 2] * sc, acc[4 * i + 3] * sc));
      d += 8;
      if (d >= 18) { d -= 18; sl++; }
    }
  }
  bar_sync(1, 256);
  {
    const int tok = tid & 127;
    float* red = reinterpret_cast<float*>(smem + K1_RED);
#pragma unroll
    for (int i = 0; i < 6; i++) {
      const int sl = (tid >> 7) + 2 * i, slot = nt * 12 + sl;
      const uint32_t a = sb + sl * 6144 + (tok >> 3) * 384 + (tok & 7) * 16;
      const uint4 v0 = lds128(a), v1 = lds128(a + 128);
      const uint32_t v2 = lds32(a + 256);
      uint32_t pad = 0;
      if (slot >= 64) pad = VPAD_ONE;
      else if (slot >= 32) pad = poly_block((tok >> 3) & 7) ? KPAD_POLY : 0u;
      sts128(a + 256, make_uint4(v2, pad, 0u, 0u));
      float n2 = 0.f;
      const uint32_t w[9] = {v0.x, v0.y, v0.z, v0.w, v1.x, v1.y, v1.z, v1.w, v2};
#pragma unroll
      for (int j = 0; j < 9; j++) { n2 = fmaf(bf_lo(w[j]), bf_lo(w[j]), n2); n2 = fmaf(bf_hi(w[j]), bf_hi(w[j]), n2); }
      const uint32_t mx = __reduce_max_sync(0xffffffffu, __float_as_uint(n2) & 0x7FFFFFFFu);
      if (lane == 0) red[sl * 4 + warp] = __uint_as_float(mx);
    }
    fence_async_smem();
    bar_sync(1, 256);
    if (tid == 0) {
      for (int sl = 0; sl < 12; sl++)
        bulk_s2g(g_qkvp + (size_t)(nt * 12 + sl) * SLOT_BYTES + (size_t)rb * 6144, sb + sl * 6144, 6144);
      bulk_commit();
    }
    if (tid >= 32 && tid < 44) {
      const int sl = tid - 32, slot = nt * 12 + sl;
      const uint32_t* r = reinterpret_cast<const uint32_t*>(red) + sl * 4;
      if (slot < 64) g_nrm[rb * 64 + slot] = __uint_as_float(max(max(r[0], r[1]), max(r[2], r[3])));
    }
    if (tid == 0) bulk_wait_all();
  }
  TL(1, 3);
}

constexpr int K2_K = 0, K2_V = SLOT_BYTES, K2_Q = 2 * SLOT_BYTES, K2_BAR = K2_Q + 512 * 48, K2_SMEM = K2_BAR + 8 * 17 + 8;
constexpr uint32_t EXP_C2 = 0x3EA93EA9u, EXP_C1 = 0x3B4E3B4Eu, EXP_C0 = 0x3F2C3F2Cu;
constexpr int K2_TD = 8 * 384 / 16;

__device__ __forceinline__ uint32_t opaque(uint32_t v) { uint32_t r; asm volatile("mov.b32 %0, %1;" : "=r"(r) : "r"(v)); return r; }

__device__ __forceinline__ void attn_qk(float (&S)[32], const uint32_t (&q)[8], uint64_t kd) {
  wgmma_rs0_n64(S, q[0], q[1], q[2], q[3], kd);
  wgmma_rs_n64(S, q[4], q[5], q[6], q[7], kd + 16, 1);
}
__device__ __forceinline__ void attn_pv(float (&O)[12], const uint32_t (&P)[16], uint64_t vd) {
#pragma unroll
  for (int kk = 0; kk < 4; kk++) wgmma_rs_n24_tb(O, P[4 * kk], P[4 * kk + 1], P[4 * kk + 2], P[4 * kk + 3], vd + kk * 48, 1);
}
__device__ __forceinline__ void attn_exp(float (&S)[32], uint32_t c2, uint32_t cone) {
#pragma unroll
  for (int b = 0; b < 8; b++) {
    if (poly_block(b)) {
#pragma unroll
      for (int h = 0; h < 2; h++) {
        uint32_t w, y;
        asm("prmt.b32 %0, %1, %2, 0x5410;" : "=r"(w) : "r"(__float_as_uint(S[4 * b + 2 * h])), "r"(__float_as_uint(S[4 * b + 2 * h + 1])));
        asm("lop3.b32 %0, %1, 0x007F007F, %2, 0xEA;" : "=r"(y) : "r"(w), "r"(cone));
        const uint32_t p = hfma2(hfma2(y, c2, EXP_C1), y, EXP_C0);
        S[4 * b + 2 * h] = __uint_as_float(w);
        S[4 * b + 2 * h + 1] = __uint_as_float(p);
      }
    } else {
#pragma unroll
      for (int j = 0; j < 4; j++) S[4 * b + j] = ex2(S[4 * b + j]);
    }
  }
}
__device__ __forceinline__ void attn_pack(const float (&S)[32], uint32_t (&P)[16]) {
#pragma unroll
  for (int i = 0; i < 16; i++) {
    if (poly_block(i >> 1)) asm("lop3.b32 %0, %1, %2, 0xFF80FF80, 0xE4;" : "=r"(P[i]) : "r"(__float_as_uint(S[2 * i])), "r"(__float_as_uint(S[2 * i + 1])));
    else P[i] = pack_bf16(S[2 * i], S[2 * i + 1]);
  }
}

template <bool WAIT>
__device__ __forceinline__ void attn_fast_pass(float (&O)[12], const uint32_t (&q)[8], uint64_t kd, uint64_t vd, uint32_t bar) {
  float S[32]; uint32_t P[16];
  const uint32_t c2 = opaque(EXP_C2), cone = opaque(0x3F803F80u);
  if (WAIT) mbar_wait(bar, 0);
  wg_fence();
  attn_qk(S, q, kd);
  wg_commit();
  wg_wait<0>();
  fence_regs(S);
  attn_exp(S, c2, cone);
  attn_pack(S, P);
  auto step = [&]() {
    kd += K2_TD;
    fence_regs(P); fence_regs(O);
    wg_fence();
    attn_qk(S, q, kd);
    wg_commit();
    attn_pv(O, P, vd);
    wg_commit();
    vd += K2_TD;
    wg_wait<1>();
    fence_regs(S);
    attn_exp(S, c2, cone);
    fence_regs(S);
    wg_wait<0>();
    fence_regs(S); fence_regs(O);
    attn_pack(S, P);
  };
#pragma unroll 1
  for (int c = 1; c < 16; c++) {
    step();
    if (WAIT) mbar_wait(bar + 8 * c, 0);
    step();
  }
  step();
  fence_regs(P); fence_regs(O);
  wg_fence();
  attn_pv(O, P, vd);
  wg_commit();
  wg_wait<0>();
  fence_regs(O);
}

__device__ __forceinline__ void attn_safe_pass(float (&O)[12], const uint32_t (&q)[8], uint64_t kd, uint64_t vd, uint32_t bar) {
  float S[32]; uint32_t P[16];
  float m0 = -INFINITY, m1 = -INFINITY;
#pragma unroll 1
  for (int j = 0; j < 32; j++) {
    if ((j & 1) == 0) mbar_wait(bar + 8 * (j >> 1), 0);
    wg_fence();
    attn_qk(S, q, kd);
    wg_commit();
    wg_wait<0>();
    fence_regs(S);
    float x0 = m0, x1 = m1;
#pragma unroll
    for (int b = 0; b < 8; b++) { x0 = fmaxf(x0, fmaxf(S[4 * b], S[4 * b + 1])); x1 = fmaxf(x1, fmaxf(S[4 * b + 2], S[4 * b + 3])); }
    x0 = fmaxf(x0, __shfl_xor_sync(0xffffffffu, x0, 1)); x0 = fmaxf(x0, __shfl_xor_sync(0xffffffffu, x0, 2));
    x1 = fmaxf(x1, __shfl_xor_sync(0xffffffffu, x1, 1)); x1 = fmaxf(x1, __shfl_xor_sync(0xffffffffu, x1, 2));
    const float a0 = ex2(m0 - x0), a1 = ex2(m1 - x1);
    m0 = x0; m1 = x1;
#pragma unroll
    for (int b = 0; b < 3; b++) { O[4 * b] *= a0; O[4 * b + 1] *= a0; O[4 * b + 2] *= a1; O[4 * b + 3] *= a1; }
#pragma unroll
    for (int b = 0; b < 8; b++) {
      P[2 * b] = pack_bf16(ex2(S[4 * b] - m0), ex2(S[4 * b + 1] - m0));
      P[2 * b + 1] = pack_bf16(ex2(S[4 * b + 2] - m1), ex2(S[4 * b + 3] - m1));
    }
    fence_regs(P); fence_regs(O);
    wg_fence();
    attn_pv(O, P, vd);
    wg_commit();
    wg_wait<0>();
    fence_regs(O);
    kd += K2_TD; vd += K2_TD;
  }
}

__global__ void __launch_bounds__(512, 1) k2_attn(const bf16* __restrict__ wo, const bf16* __restrict__ w1, const bf16* __restrict__ w2) {
  extern __shared__ __align__(1024) uint8_t smem[];
  const uint32_t sb = s2u(smem);
  const int head = blockIdx.x >> 2, qg = blockIdx.x & 3;
  const int tid = threadIdx.x, wg = __shfl_sync(0xffffffffu, tid >> 7, 0), warp = (tid >> 5) & 3, lane = tid & 31, g = lane >> 2, q4 = lane & 3;
  const uint32_t bar = sb + K2_BAR;
  TL(2, 0);
  if (tid == 0) {
    for (int i = 0; i < 17; i++) mbar_init(bar + 8 * i, 1);
    fence_barrier_init();
  }
  pdl_launch();
  if (tid == 32) {
    const char* a = reinterpret_cast<const char*>(w1) + (size_t)blockIdx.x * (DM * FF * 2 / 128);
    const char* b = reinterpret_cast<const char*>(w2) + (size_t)blockIdx.x * (DM * FF * 2 / 128);
    const char* c = reinterpret_cast<const char*>(wo) + (size_t)blockIdx.x * (DM * DM * 2 / 128);
    asm volatile("cp.async.bulk.prefetch.L2.global [%0], %1;" :: "l"(c), "r"(DM * DM * 2 / 128) : "memory");
    asm volatile("cp.async.bulk.prefetch.L2.global [%0], %1;" :: "l"(a), "r"(DM * FF * 2 / 128) : "memory");
    asm volatile("cp.async.bulk.prefetch.L2.global [%0], %1;" :: "l"(b), "r"(DM * FF * 2 / 128) : "memory");
  }
  pdl_wait();
  if (tid == 0) {
    const uint8_t* Qg = g_qkvp + (size_t)head * SLOT_BYTES + (size_t)qg * 512 * 48;
    const uint8_t* Kg = g_qkvp + (size_t)(32 + head) * SLOT_BYTES;
    const uint8_t* Vg = g_qkvp + (size_t)(64 + head) * SLOT_BYTES;
    mbar_expect(bar + 8 * 16, 512 * 48);
    bulk_g2s(sb + K2_Q, Qg, 512 * 48, bar + 8 * 16);
    for (int c = 0; c < 16; c++) {
      mbar_expect(bar + 8 * c, 2 * 6144);
      bulk_g2s(sb + K2_K + c * 6144, Kg + c * 6144, 6144, bar + 8 * c);
      bulk_g2s(sb + K2_V + c * 6144, Vg + c * 6144, 6144, bar + 8 * c);
    }
  }
  bool fast;
  {
    uint32_t v = 0;
    if (lane < 16) v = __float_as_uint(g_nrm[lane * 64 + 32 + head]);
    const uint32_t km = __reduce_max_sync(0xffffffffu, v);
    v = 0;
    if (lane < 4) v = __float_as_uint(g_nrm[(qg * 4 + lane) * 64 + head]);
    const uint32_t qm = __reduce_max_sync(0xffffffffu, v);
    fast = __uint_as_float(km) * __uint_as_float(qm) <= 4096.0f;
  }
  __syncthreads();
  TL(2, 1);
  const uint64_t kd = mkdesc(sb + K2_K, 128, 384, 0);
  const uint64_t vd = mkdesc(sb + K2_V, 384, 128, 0);
  mbar_wait(bar + 8 * 16, 0);
#pragma unroll 1
  for (int it = 0; it < 2; it++) {
    const int qt = wg * 2 + it;
    uint32_t q[8];
    {
      const uint32_t base = sb + K2_Q + (qt * 8 + warp * 2) * 384 + g * 16 + q4 * 4;
#pragma unroll
      for (int j = 0; j < 3; j++) { q[2 * j] = lds32(base + j * 128); q[2 * j + 1] = lds32(base + 384 + j * 128); }
      if (fast && q4 == 1) { q[4] = 0x3F803F80u; q[5] = 0x3F803F80u; }
      q[6] = opaque(0u); q[7] = opaque(0u);
    }
    float O[12];
#pragma unroll
    for (int i = 0; i < 12; i++) O[i] = 0.f;
    if (fast) {
      if (it == 0) attn_fast_pass<true>(O, q, kd, vd, bar);
      else attn_fast_pass<false>(O, q, kd, vd, bar);
    } else {
      attn_safe_pass(O, q, kd, vd, bar);
    }
    const float l0 = __shfl_sync(0xffffffffu, O[8], (lane & ~3) | 1), l1 = __shfl_sync(0xffffffffu, O[10], (lane & ~3) | 1);
    const float r0 = __frcp_rn(l0), r1 = __frcp_rn(l1);
    const int row = qg * 512 + qt * 64 + warp * 16 + g;
    uint32_t* o0 = reinterpret_cast<uint32_t*>(g_o + (size_t)row * DM + head * DHEAD + q4 * 2);
    uint32_t* o1 = o0 + 8 * DM / 2;
    o0[0] = pack_bf16(O[0] * r0, O[1] * r0);  o1[0] = pack_bf16(O[2] * r1, O[3] * r1);
    o0[4] = pack_bf16(O[4] * r0, O[5] * r0);  o1[4] = pack_bf16(O[6] * r1, O[7] * r1);
    if (q4 == 0) { o0[8] = pack_bf16(O[8] * r0, O[9] * r0);  o1[8] = pack_bf16(O[10] * r1, O[11] * r1); }
  }
  TL(2, 3);
}

constexpr int K3_NST = 4;
constexpr int K3_W = 0, K3_A = 147456, K3_BAR = K3_A + K3_NST * 16384, K3_SMEM = K3_BAR + 8 * (1 + 2 * K3_NST) + 8;

__global__ void __launch_bounds__(288, 1) k3_wo(const __grid_constant__ CUtensorMap tm_o, const __grid_constant__ CUtensorMap tm_wo, const bf16* __restrict__ x) {
  extern __shared__ __align__(1024) uint8_t smem[];
  const uint32_t sb = s2u(smem);
  const int tid = threadIdx.x, nt = blockIdx.x & 7, rb = blockIdx.x >> 3;
  const uint32_t bw = sb + K3_BAR, baf = bw + 8, bae = baf + 8 * K3_NST;
  TL(3, 0);
  if (tid == 256) {
    mbar_init(bw, 1);
    for (int i = 0; i < K3_NST; i++) { mbar_init(baf + 8 * i, 1); mbar_init(bae + 8 * i, 2); }
    fence_barrier_init();
    tmap_prefetch(&tm_o); tmap_prefetch(&tm_wo);
  }
  __syncthreads();
  pdl_launch();
  if (tid >= 256) {
    if (tid == 256) {
      mbar_expect(bw, 147456);
      for (int c = 0; c < 9; c++)
        for (int g = 0; g < 2; g++) tma2d(sb + K3_W + c * 16384 + g * 8192, &tm_wo, nt * 72 + g * 64, c * 64, bw);
      pdl_wait();
      for (int c = 0; c < 9; c++) {
        const int s = c % K3_NST;
        if (c >= K3_NST) mbar_wait(bae + 8 * s, (c / K3_NST - 1) & 1);
        mbar_expect(baf + 8 * s, 16384);
        tma2d(sb + K3_A + s * 16384, &tm_o, c * 64, rb * 128, baf + 8 * s);
      }
    }
    return;
  }
  const int wg = __shfl_sync(0xffffffffu, tid >> 7, 0), wtid = tid & 127, warp = (tid >> 5) & 3, lane = tid & 31, g = lane >> 2, q4 = lane & 3;
  const int row = rb * 128 + wg * 64 + warp * 16 + g, col = nt * 72 + 2 * q4;
  uint32_t xr[18];
  {
    const uint32_t* p0 = reinterpret_cast<const uint32_t*>(x + (size_t)row * DM + col);
#pragma unroll
    for (int i = 0; i < 9; i++) { xr[2 * i] = __ldg(p0 + 4 * i); xr[2 * i + 1] = __ldg(p0 + 8 * DM / 2 + 4 * i); }
  }
  pdl_wait();
  TL(3, 1);
  uint32_t ga[9], c1[9], sh[9];
  {
    const uint32_t* m32 = reinterpret_cast<const uint32_t*>(g_mod) + col / 2;
#pragma unroll
    for (int i = 0; i < 9; i++) { ga[i] = m32[2 * 288 + 4 * i]; sh[i] = m32[3 * 288 + 4 * i]; c1[i] = hadd2(m32[4 * 288 + 4 * i], 0x3F803F80u); }
  }
  float acc[36];
  const uint64_t da0 = mkdesc(sb + K3_A + wg * 8192, 16, 1024, 1);
  const uint64_t db0 = mkdesc(sb + K3_W, 8192, 1024, 1);
  mbar_wait(bw, 0);
#pragma unroll 1
  for (int c = 0; c < 9; c++) {
    const int s = c % K3_NST;
    mbar_wait(baf + 8 * s, (c / K3_NST) & 1);
    wg_fence();
#pragma unroll
    for (int j = 0; j < 4; j++) wgmma_ss_n72_tb(acc, da0 + (uint64_t)(s * 1024 + j * 2), db0 + (uint64_t)(c * 1024 + j * 128), (c | j) != 0);
    wg_commit();
    if (c > 0) { wg_wait<1>(); if (wtid == 0) mbar_arrive(bae + 8 * ((c - 1) % K3_NST)); }
  }
  wg_wait<0>();
  fence_regs(acc);
  TL(3, 2);
  float s0 = 0.f, s1 = 0.f;
#pragma unroll
  for (int i = 0; i < 9; i++) {
    const float g0 = bf_lo(ga[i]), g1 = bf_hi(ga[i]);
    acc[4 * i]     = bf_round(bf_lo(xr[2 * i])     + bf_round(g0 * bf_round(acc[4 * i])));
    acc[4 * i + 1] = bf_round(bf_hi(xr[2 * i])     + bf_round(g1 * bf_round(acc[4 * i + 1])));
    acc[4 * i + 2] = bf_round(bf_lo(xr[2 * i + 1]) + bf_round(g0 * bf_round(acc[4 * i + 2])));
    acc[4 * i + 3] = bf_round(bf_hi(xr[2 * i + 1]) + bf_round(g1 * bf_round(acc[4 * i + 3])));
    s0 += acc[4 * i] + acc[4 * i + 1]; s1 += acc[4 * i + 2] + acc[4 * i + 3];
  }
  s0 += __shfl_xor_sync(0xffffffffu, s0, 1); s0 += __shfl_xor_sync(0xffffffffu, s0, 2);
  s1 += __shfl_xor_sync(0xffffffffu, s1, 1); s1 += __shfl_xor_sync(0xffffffffu, s1, 2);
  const float m0 = s0 * (1.0f / 72), m1 = s1 * (1.0f / 72);
  float v0 = 0.f, v1 = 0.f;
#pragma unroll
  for (int i = 0; i < 9; i++) {
    float d;
    d = acc[4 * i] - m0; v0 = fmaf(d, d, v0); d = acc[4 * i + 1] - m0; v0 = fmaf(d, d, v0);
    d = acc[4 * i + 2] - m1; v1 = fmaf(d, d, v1); d = acc[4 * i + 3] - m1; v1 = fmaf(d, d, v1);
  }
  v0 += __shfl_xor_sync(0xffffffffu, v0, 1); v0 += __shfl_xor_sync(0xffffffffu, v0, 2);
  v1 += __shfl_xor_sync(0xffffffffu, v1, 1); v1 += __shfl_xor_sync(0xffffffffu, v1, 2);
  if (q4 == 0) { g_stats[row * 8 + nt] = make_float2(m0, v0); g_stats[(row + 8) * 8 + nt] = make_float2(m1, v1); }
  {
    uint32_t* p0 = reinterpret_cast<uint32_t*>(g_x2 + (size_t)row * DM + col);
#pragma unroll
    for (int i = 0; i < 9; i++) { p0[4 * i] = pack_bf16(acc[4 * i], acc[4 * i + 1]); p0[8 * DM / 2 + 4 * i] = pack_bf16(acc[4 * i + 2], acc[4 * i + 3]); }
  }
  __threadfence();
  bar_sync(1, 256);
  if (tid == 0) epoch_barrier(&g_cnt[rb], 8);
  bar_sync(1, 256);
  float mean0, mean1, rs0, rs1;
  {
    const float4 a = __ldcg(reinterpret_cast<const float4*>(g_stats + row * 8) + q4);
    const float4 b = __ldcg(reinterpret_cast<const float4*>(g_stats + (row + 8) * 8) + q4);
    float sa = a.x + a.z, sb_ = b.x + b.z;
    sa += __shfl_xor_sync(0xffffffffu, sa, 1); sa += __shfl_xor_sync(0xffffffffu, sa, 2);
    sb_ += __shfl_xor_sync(0xffffffffu, sb_, 1); sb_ += __shfl_xor_sync(0xffffffffu, sb_, 2);
    mean0 = sa * 0.125f; mean1 = sb_ * 0.125f;
    float ma = a.y + a.w + 72.f * ((a.x - mean0) * (a.x - mean0) + (a.z - mean0) * (a.z - mean0));
    float mb = b.y + b.w + 72.f * ((b.x - mean1) * (b.x - mean1) + (b.z - mean1) * (b.z - mean1));
    ma += __shfl_xor_sync(0xffffffffu, ma, 1); ma += __shfl_xor_sync(0xffffffffu, ma, 2);
    mb += __shfl_xor_sync(0xffffffffu, mb, 1); mb += __shfl_xor_sync(0xffffffffu, mb, 2);
    rs0 = 1.0f / sqrtf(ma * (1.0f / DM) + 1e-5f); rs1 = 1.0f / sqrtf(mb * (1.0f / DM) + 1e-5f);
  }
  {
    uint32_t* p0 = reinterpret_cast<uint32_t*>(g_h2 + (size_t)row * DM + col);
#pragma unroll
    for (int i = 0; i < 9; i++) {
      p0[4 * i] = hfma2(pack_bf16((acc[4 * i] - mean0) * rs0, (acc[4 * i + 1] - mean0) * rs0), c1[i], sh[i]);
      p0[8 * DM / 2 + 4 * i] = hfma2(pack_bf16((acc[4 * i + 2] - mean1) * rs1, (acc[4 * i + 3] - mean1) * rs1), c1[i], sh[i]);
    }
  }
  TL(3, 3);
}

constexpr int K4_NST = 3;
constexpr int K4_A = 0, K4_B = 147456, K4_BAR = K4_B + K4_NST * 24576, K4_SMEM = K4_BAR + 8 * (9 + 2 * K4_NST) + 8;

__device__ __forceinline__ float silu_f(float v) { const float h = 0.5f * v; return fmaf(h, tanh_fast(h), h); }

template <int P>
__device__ __forceinline__ void k4_epi(const float (&acc)[96], bf16* hp) {
  constexpr int B = 16 * (P >> 1) + 2 * (P & 1);
  uint4 r;
  r.x = pack_bf16(silu_f(acc[B + 0]), silu_f(acc[B + 1]));
  r.y = pack_bf16(silu_f(acc[B + 4]), silu_f(acc[B + 5]));
  r.z = pack_bf16(silu_f(acc[B + 8]), silu_f(acc[B + 9]));
  r.w = pack_bf16(silu_f(acc[B + 12]), silu_f(acc[B + 13]));
  asm volatile("st.global.v4.b32 [%0], {%1,%2,%3,%4};" :: "l"(hp + (P & 1) * 8 * FF + 32 * (P >> 1)), "r"(r.x), "r"(r.y), "r"(r.z), "r"(r.w) : "memory");
}

template <int T, bool EPI>
__device__ __forceinline__ void k4_tile(float (&cur)[96], const float (&prev)[96], bf16* hprev, uint64_t da0, uint64_t db0,
                                        uint32_t ba, uint32_t bbf, uint32_t bbe, int wtid) {
#pragma unroll
  for (int c = 0; c < 9; c++) {
    const int st = T * 9 + c, s = st % K4_NST;
    if (T == 0) mbar_wait(ba + 8 * c, 0);
    mbar_wait(bbf + 8 * s, (st / K4_NST) & 1);
    wg_fence();
#pragma unroll
    for (int j = 0; j < 4; j++) {
      if (c == 0 && j == 0) wgmma_ss0_n192_tb(cur, da0, db0 + (uint64_t)(s * 1536));
      else wgmma_ss_n192_tb(cur, da0 + (uint64_t)(c * 1024 + j * 2), db0 + (uint64_t)(s * 1536 + j * 128), 1);
    }
    wg_commit();
    if (EPI) {
      if (c == 0) { k4_epi<0>(prev, hprev); }
      if (c == 1) { k4_epi<1>(prev, hprev); k4_epi<2>(prev, hprev); }
      if (c == 2) { k4_epi<3>(prev, hprev); }
      if (c == 3) { k4_epi<4>(prev, hprev); k4_epi<5>(prev, hprev); }
      if (c == 4) { k4_epi<6>(prev, hprev); }
      if (c == 5) { k4_epi<7>(prev, hprev); k4_epi<8>(prev, hprev); }
      if (c == 6) { k4_epi<9>(prev, hprev); }
      if (c == 7) { k4_epi<10>(prev, hprev); k4_epi<11>(prev, hprev); }
    }
    if (st > 0) { wg_wait<1>(); if (wtid == 0) mbar_arrive(bbe + 8 * ((st - 1) % K4_NST)); }
  }
}

__global__ void __launch_bounds__(384, 1) k4_mlp1(const __grid_constant__ CUtensorMap tm_h2, const __grid_constant__ CUtensorMap tm_w1) {
  extern __shared__ __align__(1024) uint8_t smem[];
  const uint32_t sb = s2u(smem);
  const int tid = threadIdx.x, rb = blockIdx.x & 15, fs = blockIdx.x >> 4;
  const uint32_t ba = sb + K4_BAR, bbf = ba + 72, bbe = bbf + 8 * K4_NST;
  TL(4, 0);
  if (tid == 0) {
    for (int i = 0; i < 9; i++) mbar_init(ba + 8 * i, 1);
    for (int i = 0; i < K4_NST; i++) { mbar_init(bbf + 8 * i, 1); mbar_init(bbe + 8 * i, 2); }
    fence_barrier_init();
    tmap_prefetch(&tm_h2); tmap_prefetch(&tm_w1);
  }
  __syncthreads();
  pdl_launch();
  if (tid < 128) {
    reg_dec<24>();
    if (tid == 0) {
      for (int st = 0; st < 27; st++) {
        const int s = st % K4_NST, t = st / 9, c = st % 9;
        if (st == K4_NST) {
          pdl_wait();
          for (int cc = 0; cc < 9; cc++) { mbar_expect(ba + 8 * cc, 16384); tma2d(sb + K4_A + cc * 16384, &tm_h2, cc * 64, rb * 128, ba + 8 * cc); }
        }
        if (st >= K4_NST) mbar_wait(bbe + 8 * s, (st / K4_NST - 1) & 1);
        mbar_expect(bbf + 8 * s, 24576);
        for (int g = 0; g < 3; g++) tma2d(sb + K4_B + s * 24576 + g * 8192, &tm_w1, fs * 576 + t * 192 + g * 64, c * 64, bbf + 8 * s);
      }
    }
  } else {
    reg_inc<240>();
    const int wg = __shfl_sync(0xffffffffu, (tid >> 7) - 1, 0), wtid = tid & 127, warp = (tid >> 5) & 3, lane = tid & 31, g = lane >> 2, q4 = lane & 3;
    const uint64_t da0 = mkdesc(sb + K4_A + wg * 8192, 16, 1024, 1);
    const uint64_t db0 = mkdesc(sb + K4_B, 8192, 1024, 1);
    bf16* hp = g_H + (size_t)(rb * 128 + wg * 64 + warp * 16 + g) * FF + fs * 576 + q4 * 8;
    float a0[96], a1[96];
    TLT(4, 1, 128);
    k4_tile<0, false>(a0, a1, hp, da0, db0, ba, bbf, bbe, wtid);
    wg_wait<0>(); fence_regs(a0);
    k4_tile<1, true>(a1, a0, hp, da0, db0, ba, bbf, bbe, wtid);
    wg_wait<0>(); fence_regs(a1);
    k4_tile<2, true>(a0, a1, hp + 192, da0, db0, ba, bbf, bbe, wtid);
    wg_wait<0>(); fence_regs(a0);
    TLT(4, 2, 128);
    k4_epi<0>(a0, hp + 384); k4_epi<1>(a0, hp + 384); k4_epi<2>(a0, hp + 384); k4_epi<3>(a0, hp + 384);
    k4_epi<4>(a0, hp + 384); k4_epi<5>(a0, hp + 384); k4_epi<6>(a0, hp + 384); k4_epi<7>(a0, hp + 384);
    k4_epi<8>(a0, hp + 384); k4_epi<9>(a0, hp + 384); k4_epi<10>(a0, hp + 384); k4_epi<11>(a0, hp + 384);
    TLT(4, 3, 128);
  }
}

constexpr int K5_NST = 4;
constexpr int K5_STAGE = 16384 + 36864;
constexpr int K5_BAR = K5_NST * K5_STAGE, K5_SMEM = K5_BAR + 8 * (2 * K5_NST) + 8;

template <int I> __device__ __forceinline__ float& k5_acc(float (&a)[80], float (&b)[64]) { if constexpr (I < 80) return a[I]; else return b[I - 80]; }

template <int KS, int QD, int I>
__device__ __forceinline__ void k5_send(float (&a)[80], float (&b)[64], float4* dst) {
  if constexpr (I < 9) {
    constexpr int B = 9 * QD + I;
    __stcg(dst + I * 256, make_float4(k5_acc<4 * B>(a, b), k5_acc<4 * B + 1>(a, b), k5_acc<4 * B + 2>(a, b), k5_acc<4 * B + 3>(a, b)));
    k5_send<KS, QD, I + 1>(a, b, dst);
  }
}
template <int KS, int I>
__device__ __forceinline__ void k5_gather(float (&a)[80], float (&b)[64], const float4* src) {
  if constexpr (I < 9) {
    constexpr int B = 9 * KS + I;
    const float4 p = __ldcg(src + I * 256);
    k5_acc<4 * B>(a, b) += p.x; k5_acc<4 * B + 1>(a, b) += p.y; k5_acc<4 * B + 2>(a, b) += p.z; k5_acc<4 * B + 3>(a, b) += p.w;
    k5_gather<KS, I + 1>(a, b, src);
  }
}
template <int KS, int I>
__device__ __forceinline__ void k5_final(float (&a)[80], float (&b)[64], const uint32_t (&xr)[18], const uint32_t (&gb)[9], uint32_t* o0) {
  if constexpr (I < 9) {
    constexpr int B = 9 * KS + I;
    const float v0 = k5_acc<4 * B>(a, b), v1 = k5_acc<4 * B + 1>(a, b), v2 = k5_acc<4 * B + 2>(a, b), v3 = k5_acc<4 * B + 3>(a, b);
    const float g0 = bf_lo(gb[I]), g1 = bf_hi(gb[I]);
    o0[4 * I] = pack_bf16(bf_lo(xr[2 * I]) + bf_round(g0 * bf_round(v0)), bf_hi(xr[2 * I]) + bf_round(g1 * bf_round(v1)));
    o0[8 * DM / 2 + 4 * I] = pack_bf16(bf_lo(xr[2 * I + 1]) + bf_round(g0 * bf_round(v2)), bf_hi(xr[2 * I + 1]) + bf_round(g1 * bf_round(v3)));
    k5_final<KS, I + 1>(a, b, xr, gb, o0);
  }
}
template <int KS>
__device__ __forceinline__ void k5_reduce(float (&a)[80], float (&b)[64], int tile, int ctid, int row, int nh, int q4, bf16* out) {
  float4* base = g_part + (size_t)tile * (4 * 4 * 9 * 256) + ctid;
  if (KS != 0) k5_send<KS, 0, 0>(a, b, base + (KS * 4 + 0) * 9 * 256);
  if (KS != 1) k5_send<KS, 1, 0>(a, b, base + (KS * 4 + 1) * 9 * 256);
  if (KS != 2) k5_send<KS, 2, 0>(a, b, base + (KS * 4 + 2) * 9 * 256);
  if (KS != 3) k5_send<KS, 3, 0>(a, b, base + (KS * 4 + 3) * 9 * 256);
  const int col = nh * 288 + KS * 72 + 2 * q4;
  uint32_t xr[18], gb[9];
  {
    const uint32_t* p0 = reinterpret_cast<const uint32_t*>(g_x2 + (size_t)row * DM + col);
    const uint32_t* m32 = reinterpret_cast<const uint32_t*>(g_mod) + 5 * 288 + col / 2;
#pragma unroll
    for (int i = 0; i < 9; i++) { xr[2 * i] = __ldcg(p0 + 4 * i); xr[2 * i + 1] = __ldcg(p0 + 8 * DM / 2 + 4 * i); gb[i] = __ldcg(m32 + 4 * i); }
  }
  __threadfence();
  bar_sync(1, 256);
  if (ctid == 0) epoch_barrier(&g_cnt[32 + tile], 4);
  bar_sync(1, 256);
#pragma unroll
  for (int s = 0; s < 3; s++) {
    const int src = s + (s >= KS ? 1 : 0);
    k5_gather<KS, 0>(a, b, base + (src * 4 + KS) * 9 * 256);
  }
  k5_final<KS, 0>(a, b, xr, gb, reinterpret_cast<uint32_t*>(out + (size_t)row * DM + col));
}

__global__ void __launch_bounds__(384, 1) k5_mlp2(const __grid_constant__ CUtensorMap tm_h, const __grid_constant__ CUtensorMap tm_w2, bf16* __restrict__ out) {
  extern __shared__ __align__(1024) uint8_t smem[];
  const uint32_t sb = s2u(smem);
  const int tid = threadIdx.x, rb = blockIdx.x & 15, nh = (blockIdx.x >> 4) & 1, ks = blockIdx.x >> 5;
  const uint32_t bf = sb + K5_BAR, be = bf + 8 * K5_NST;
  TL(5, 0);
  if (tid == 0) {
    for (int i = 0; i < K5_NST; i++) { mbar_init(bf + 8 * i, 1); mbar_init(be + 8 * i, 2); }
    fence_barrier_init();
    tmap_prefetch(&tm_h); tmap_prefetch(&tm_w2);
  }
  __syncthreads();
  if (tid < 128) {
    reg_dec<24>();
    if (tid == 0) {
      for (int st = 0; st < K5_NST; st++) {
        mbar_expect(bf + 8 * st, K5_STAGE);
        for (int g = 0; g < 9; g++) tma5d(sb + st * K5_STAGE + 16384 + g * 4096, &tm_w2, nh * 288 + g * 32, 0, 0, 0, (ks * 18 + st) * 2, bf + 8 * st);
      }
      pdl_wait();
      for (int st = 0; st < 18; st++) {
        const int s = st % K5_NST;
        if (st >= K5_NST) {
          mbar_wait(be + 8 * s, (st / K5_NST - 1) & 1);
          mbar_expect(bf + 8 * s, K5_STAGE);
          for (int g = 0; g < 9; g++) tma5d(sb + s * K5_STAGE + 16384 + g * 4096, &tm_w2, nh * 288 + g * 32, 0, 0, 0, (ks * 18 + st) * 2, bf + 8 * s);
        }
        tma2d(sb + s * K5_STAGE, &tm_h, (ks * 18 + st) * 64, rb * 128, bf + 8 * s);
      }
    }
  } else {
    reg_inc<240>();
    const int ctid = tid - 128, wg = __shfl_sync(0xffffffffu, ctid >> 7, 0), wtid = tid & 127, warp = (tid >> 5) & 3, lane = tid & 31, g = lane >> 2, q4 = lane & 3;
    float a[80], b[64];
#pragma unroll
    for (int i = 0; i < 80; i++) a[i] = 0.f;
#pragma unroll
    for (int i = 0; i < 64; i++) b[i] = 0.f;
    const uint64_t da0 = mkdesc(sb + wg * 8192, 16, 1024, 1);
    const uint64_t db0 = mkdesc(sb + 16384, 4096, 512, 2);
#pragma unroll 1
    for (int st = 0; st < 18; st++) {
      const int s = st % K5_NST;
      mbar_wait(bf + 8 * s, (st / K5_NST) & 1);
      wg_fence();
#pragma unroll
      for (int j = 0; j < 4; j++) {
        const uint64_t da = da0 + (uint64_t)(s * (K5_STAGE / 16) + j * 2), db = db0 + (uint64_t)(s * (K5_STAGE / 16) + j * 64);
        wgmma_ss_n160_tb(a, da, db, 1);
        wgmma_ss_n128_tb(b, da, db + 5 * 256, 1);
      }
      wg_commit();
      if (st > 0) { wg_wait<1>(); if (wtid == 0) mbar_arrive(be + 8 * ((st - 1) % K5_NST)); }
    }
    wg_wait<0>();
    fence_regs(a); fence_regs(b);
    pdl_wait();
    TLT(5, 2, 128);
    const int row = rb * 128 + wg * 64 + warp * 16 + g, tile = rb * 2 + nh;
    if (ks == 0) k5_reduce<0>(a, b, tile, ctid, row, nh, q4, out);
    else if (ks == 1) k5_reduce<1>(a, b, tile, ctid, row, nh, q4, out);
    else if (ks == 2) k5_reduce<2>(a, b, tile, ctid, row, nh, q4, out);
    else k5_reduce<3>(a, b, tile, ctid, row, nh, q4, out);
    TLT(5, 3, 128);
  }
}

}

typedef CUresult (*EncodeTiledFn)(CUtensorMap*, CUtensorMapDataType, cuuint32_t, void*, const cuuint64_t*, const cuuint64_t*, const cuuint32_t*,
                                  const cuuint32_t*, CUtensorMapInterleave, CUtensorMapSwizzle, CUtensorMapL2promotion, CUtensorMapFloatOOBfill);

static void make_map2d(EncodeTiledFn enc, CUtensorMap* m, const void* base, int cols, int rows, int box_cols, int box_rows, CUtensorMapSwizzle sw) {
  cuuint64_t dims[2] = {(cuuint64_t)cols, (cuuint64_t)rows};
  cuuint64_t strides[1] = {(cuuint64_t)cols * 2};
  cuuint32_t box[2] = {(cuuint32_t)box_cols, (cuuint32_t)box_rows};
  cuuint32_t es[2] = {1, 1};
  enc(m, CU_TENSOR_MAP_DATA_TYPE_BFLOAT16, 2, const_cast<void*>(base), dims, strides, box, es, CU_TENSOR_MAP_INTERLEAVE_NONE, sw,
      CU_TENSOR_MAP_L2_PROMOTION_L2_128B, CU_TENSOR_MAP_FLOAT_OOB_FILL_NONE);
}

template <typename... KArgs, typename... Args>
static void launch(void (*kern)(KArgs...), int grid, int block, int smem, bool pdl, Args... args) {
  cudaLaunchConfig_t cfg = {};
  cfg.gridDim = dim3(grid); cfg.blockDim = dim3(block); cfg.dynamicSmemBytes = smem; cfg.stream = cudaStreamPerThread;
  cudaLaunchAttribute at[1];
  at[0].id = cudaLaunchAttributeProgrammaticStreamSerialization;
  at[0].val.programmaticStreamSerializationAllowed = 1;
  cfg.attrs = at; cfg.numAttrs = pdl ? 1 : 0;
  cudaLaunchKernelEx(&cfg, kern, KArgs(args)...);
}

#define USE_PDL 1

extern "C" void kernel_launch(void* const* d_in, const int* in_sizes, int n_in, void* d_out, int out_size) {
  (void)in_sizes; (void)n_in; (void)out_size;
  const bf16* x    = (const bf16*)d_in[0];
  const bf16* wqkv = (const bf16*)d_in[1];
  const bf16* wo   = (const bf16*)d_in[2];
  const bf16* w1   = (const bf16*)d_in[4];
  const bf16* w2   = (const bf16*)d_in[5];
  const bf16* c    = (const bf16*)d_in[6];
  const bf16* wmod = (const bf16*)d_in[7];
  bf16* out = (bf16*)d_out;

  static EncodeTiledFn enc = nullptr;
  if (!enc) {
    void* fn = nullptr; cudaDriverEntryPointQueryResult qr;
    cudaGetDriverEntryPoint("cuTensorMapEncodeTiled", &fn, cudaEnableDefault, &qr);
    enc = (EncodeTiledFn)fn;
    cudaFuncSetAttribute(k1_qkv, cudaFuncAttributeMaxDynamicSharedMemorySize, K1_SMEM);
    cudaFuncSetAttribute(k2_attn, cudaFuncAttributeMaxDynamicSharedMemorySize, K2_SMEM);
    cudaFuncSetAttribute(k3_wo, cudaFuncAttributeMaxDynamicSharedMemorySize, K3_SMEM);
    cudaFuncSetAttribute(k4_mlp1, cudaFuncAttributeMaxDynamicSharedMemorySize, K4_SMEM);
    cudaFuncSetAttribute(k5_mlp2, cudaFuncAttributeMaxDynamicSharedMemorySize, K5_SMEM);
  }
  void *p_xn, *p_o, *p_h2, *p_H;
  cudaGetSymbolAddress(&p_xn, g_xn); cudaGetSymbolAddress(&p_o, g_o); cudaGetSymbolAddress(&p_h2, g_h2); cudaGetSymbolAddress(&p_H, g_H);
  CUtensorMap tm_xn, tm_wqkv, tm_o, tm_wo, tm_h2, tm_w1, tm_H, tm_w2;
  make_map2d(enc, &tm_xn, p_xn, DM, SEQ, 64, 128, CU_TENSOR_MAP_SWIZZLE_128B);
  make_map2d(enc, &tm_wqkv, wqkv, 3 * DM, DM, 64, 32, CU_TENSOR_MAP_SWIZZLE_128B);
  make_map2d(enc, &tm_o, p_o, DM, SEQ, 64, 128, CU_TENSOR_MAP_SWIZZLE_128B);
  make_map2d(enc, &tm_wo, wo, DM, DM, 64, 64, CU_TENSOR_MAP_SWIZZLE_128B);
  make_map2d(enc, &tm_h2, p_h2, DM, SEQ, 64, 128, CU_TENSOR_MAP_SWIZZLE_128B);
  make_map2d(enc, &tm_w1, w1, FF, DM, 64, 64, CU_TENSOR_MAP_SWIZZLE_128B);
  make_map2d(enc, &tm_H, p_H, FF, SEQ, 64, 128, CU_TENSOR_MAP_SWIZZLE_128B);
  {
    cuuint64_t dims[5] = {(cuuint64_t)DM, 2, 4, 4, (cuuint64_t)(FF / 32)};
    cuuint64_t strides[4] = {(cuuint64_t)DM * 2, (cuuint64_t)DM * 2 * 8, (cuuint64_t)DM * 2 * 2, (cuuint64_t)DM * 2 * 32};
    cuuint32_t box[5] = {32, 2, 4, 4, 2};
    cuuint32_t es[5] = {1, 1, 1, 1, 1};
    enc(&tm_w2, CU_TENSOR_MAP_DATA_TYPE_BFLOAT16, 5, const_cast<bf16*>(w2), dims, strides, box, es, CU_TENSOR_MAP_INTERLEAVE_NONE,
        CU_TENSOR_MAP_SWIZZLE_64B, CU_TENSOR_MAP_L2_PROMOTION_L2_128B, CU_TENSOR_MAP_FLOAT_OOB_FILL_NONE);
  }
  launch(k0_mod_ln, 128, 256, 0, false, x, c, wmod);
  launch(k1_qkv, 128, 288, K1_SMEM, USE_PDL, tm_xn, tm_wqkv);
  launch(k2_attn, 128, 512, K2_SMEM, USE_PDL, wo, w1, w2);
  launch(k3_wo, 128, 288, K3_SMEM, USE_PDL, tm_o, tm_wo, x);
  launch(k4_mlp1, 128, 384, K4_SMEM, USE_PDL, tm_h2, tm_w1);
  launch(k5_mlp2, 128, 384, K5_SMEM, USE_PDL, tm_H, tm_w2, out);
}
```

```cpp
#include <cuda_runtime.h>
#include <cuda_bf16.h>
#include <cuda.h>
#include <stdint.h>

namespace {

constexpr int SEQ = 2048, DM = 576, DHEAD = 18, FF = 4608;
constexpr int SLOT_BYTES = SEQ * 48;

typedef __nv_bfloat16 bf16;

__device__ __align__(1024) bf16    g_mod[6 * DM];
__device__ __align__(1024) float   g_modp[2 * 2 * DM];
__device__ __align__(1024) uint8_t g_arena[SEQ * FF * 2];
#define g_xn   (reinterpret_cast<bf16*>(g_arena))
#define g_qkvp (g_arena + SEQ * DM * 2)
#define g_o    (reinterpret_cast<bf16*>(g_arena + SEQ * DM * 2 + 96 * SLOT_BYTES))
#define g_H    (reinterpret_cast<bf16*>(g_arena))
__device__ __align__(1024) float   g_nrm[16 * 64];
__device__ __align__(1024) bf16    g_h2[SEQ * DM];
__device__ __align__(1024) float2  g_stats[SEQ * 8];
__device__ unsigned int g_cnt[128];

__device__ __forceinline__ uint32_t s2u(const void* p) { return (uint32_t)__cvta_generic_to_shared(p); }
__device__ __forceinline__ void mbar_init(uint32_t b, uint32_t c) { asm volatile("mbarrier.init.shared::cta.b64 [%0], %1;" :: "r"(b), "r"(c) : "memory"); }
__device__ __forceinline__ void mbar_expect(uint32_t b, uint32_t bytes) { asm volatile("mbarrier.arrive.expect_tx.shared::cta.b64 _, [%0], %1;" :: "r"(b), "r"(bytes) : "memory"); }
__device__ __forceinline__ void mbar_arrive(uint32_t b) { asm volatile("mbarrier.arrive.shared::cta.b64 _, [%0];" :: "r"(b) : "memory"); }
__device__ __forceinline__ bool mbar_try(uint32_t b, uint32_t ph) {
  uint32_t ok;
  asm volatile("{\n.reg .pred p;\nmbarrier.try_wait.parity.shared::cta.b64 p, [%1], %2;\nselp.u32 %0, 1, 0, p;\n}" : "=r"(ok) : "r"(b), "r"(ph) : "memory");
  return ok != 0;
}
__device__ __forceinline__ void mbar_wait(uint32_t b, uint32_t ph) {
  if (!mbar_try(b, ph)) {
    for (int n = 0; n < (1 << 22); n++) if (mbar_try(b, ph)) break;
  }
}
__device__ __forceinline__ void fence_barrier_init() { asm volatile("fence.mbarrier_init.release.cluster;" ::: "memory"); }
__device__ __forceinline__ void fence_async_smem() { asm volatile("fence.proxy.async.shared::cta;" ::: "memory"); }
__device__ __forceinline__ void bar_sync(int id, int n) { asm volatile("bar.sync %0, %1;" :: "r"(id), "r"(n) : "memory"); }
__device__ __forceinline__ void pdl_wait() { asm volatile("griddepcontrol.wait;" ::: "memory"); }
__device__ __forceinline__ void pdl_launch() { asm volatile("griddepcontrol.launch_dependents;" ::: "memory"); }
__device__ __forceinline__ void bulk_g2s(uint32_t dst, const void* src, uint32_t bytes, uint32_t bar) {
  asm volatile("cp.async.bulk.shared::cluster.global.mbarrier::complete_tx::bytes [%0], [%1], %2, [%3];" :: "r"(dst), "l"(src), "r"(bytes), "r"(bar) : "memory");
}
__device__ __forceinline__ void bulk_s2g(void* dst, uint32_t src, uint32_t bytes) {
  asm volatile("cp.async.bulk.global.shared::cta.bulk_group [%0], [%1], %2;" :: "l"(dst), "r"(src), "r"(bytes) : "memory");
}
__device__ __forceinline__ void bulk_commit() { asm volatile("cp.async.bulk.commit_group;" ::: "memory"); }
__device__ __forceinline__ void bulk_wait_all() { asm volatile("cp.async.bulk.wait_group 0;" ::: "memory"); }
__device__ __forceinline__ void tma2d(uint32_t dst, const CUtensorMap* m, int x, int y, uint32_t bar) {
  asm volatile("cp.async.bulk.tensor.2d.shared::cluster.global.mbarrier::complete_tx::bytes [%0], [%1, {%3, %4}], [%2];"
               :: "r"(dst), "l"(m), "r"(bar), "r"(x), "r"(y) : "memory");
}
__device__ __forceinline__ void tma5d(uint32_t dst, const CUtensorMap* m, int c0, int c1, int c2, int c3, int c4, uint32_t bar) {
  asm volatile("cp.async.bulk.tensor.5d.shared::cluster.global.mbarrier::complete_tx::bytes [%0], [%1, {%3, %4, %5, %6, %7}], [%2];"
               :: "r"(dst), "l"(m), "r"(bar), "r"(c0), "r"(c1), "r"(c2), "r"(c3), "r"(c4) : "memory");
}
__device__ __forceinline__ void tma2d_mc(uint32_t dst, const CUtensorMap* m, int x, int y, uint32_t bar) {
  asm volatile("cp.async.bulk.tensor.2d.shared::cluster.global.mbarrier::complete_tx::bytes.multicast::cluster [%0], [%1, {%3, %4}], [%2], %5;"
               :: "r"(dst), "l"(m), "r"(bar), "r"(x), "r"(y), "h"((uint16_t)3) : "memory");
}
__device__ __forceinline__ void tma5d_mc(uint32_t dst, const CUtensorMap* m, int c0, int c1, int c2, int c3, int c4, uint32_t bar) {
  asm volatile("cp.async.bulk.tensor.5d.shared::cluster.global.mbarrier::complete_tx::bytes.multicast::cluster [%0], [%1, {%3, %4, %5, %6, %7}], [%2], %8;"
               :: "r"(dst), "l"(m), "r"(bar), "r"(c0), "r"(c1), "r"(c2), "r"(c3), "r"(c4), "h"((uint16_t)3) : "memory");
}
__device__ __forceinline__ void tma2d_store(const CUtensorMap* m, uint32_t src, int x, int y) {
  asm volatile("cp.async.bulk.tensor.2d.global.shared::cta.bulk_group [%0, {%2, %3}], [%1];" :: "l"(m), "r"(src), "r"(x), "r"(y) : "memory");
}
__device__ __forceinline__ uint32_t map_cta(uint32_t a, uint32_t cta) { uint32_t r; asm("mapa.shared::cluster.u32 %0, %1, %2;" : "=r"(r) : "r"(a), "r"(cta)); return r; }
__device__ __forceinline__ void mbar_arrive_remote(uint32_t ra) { asm volatile("mbarrier.arrive.shared::cluster.b64 _, [%0];" :: "r"(ra) : "memory"); }
__device__ __forceinline__ void cluster_arrive() { asm volatile("barrier.cluster.arrive.release;" ::: "memory"); }
__device__ __forceinline__ void cluster_arrive_relaxed() { asm volatile("barrier.cluster.arrive.relaxed;" ::: "memory"); }
__device__ __forceinline__ void cluster_wait() { asm volatile("barrier.cluster.wait.acquire;" ::: "memory"); }
__device__ __forceinline__ uint32_t cluster_rank() { uint32_t r; asm("mov.u32 %0, %%cluster_ctarank;" : "=r"(r)); return r; }
__device__ __forceinline__ void tma2d_prefetch(const CUtensorMap* m, int x, int y) {
  asm volatile("cp.async.bulk.prefetch.tensor.2d.L2.global [%0, {%1, %2}];" :: "l"(m), "r"(x), "r"(y) : "memory");
}
__device__ __forceinline__ void tmap_prefetch(const CUtensorMap* m) { asm volatile("prefetch.tensormap [%0];" :: "l"(m) : "memory"); }
__device__ __forceinline__ void wg_fence() { asm volatile("wgmma.fence.sync.aligned;" ::: "memory"); }
__device__ __forceinline__ void wg_commit() { asm volatile("wgmma.commit_group.sync.aligned;" ::: "memory"); }
template <int N> __device__ __forceinline__ void wg_wait() { asm volatile("wgmma.wait_group.sync.aligned %0;" :: "n"(N) : "memory"); }
__device__ __forceinline__ uint64_t mkdesc(uint32_t addr, uint32_t lbo, uint32_t sbo, int sw) {
  return (uint64_t)((addr & 0x3FFFF) >> 4) | ((uint64_t)(lbo >> 4) << 16) | ((uint64_t)(sbo >> 4) << 32) | ((uint64_t)sw << 62);
}
template <int N> __device__ __forceinline__ void fence_regs(float (&d)[N]) {
#pragma unroll
  for (int i = 0; i < N; i++) asm volatile("" : "+f"(d[i]) :: "memory");
}
template <int N> __device__ __forceinline__ void fence_regs(uint32_t (&d)[N]) {
#pragma unroll
  for (int i = 0; i < N; i++) asm volatile("" : "+r"(d[i]) :: "memory");
}
__device__ __forceinline__ float ex2(float x) { float y; asm("ex2.approx.ftz.f32 %0, %1;" : "=f"(y) : "f"(x)); return y; }
__device__ __forceinline__ float tanh_fast(float x) { float y; asm("tanh.approx.f32 %0, %1;" : "=f"(y) : "f"(x)); return y; }
__device__ __forceinline__ uint32_t pack_bf16(float lo, float hi) { uint32_t v; asm("cvt.rn.bf16x2.f32 %0, %1, %2;" : "=r"(v) : "f"(hi), "f"(lo)); return v; }
__device__ __forceinline__ float bf_lo(uint32_t v) { return __uint_as_float(v << 16); }
__device__ __forceinline__ float bf_hi(uint32_t v) { return __uint_as_float(v & 0xFFFF0000u); }
__device__ __forceinline__ float bf_round(float x) { return __bfloat162float(__float2bfloat16_rn(x)); }
__device__ __forceinline__ uint32_t hfma2(uint32_t a, uint32_t b, uint32_t c) { uint32_t d; asm("fma.rn.bf16x2 %0, %1, %2, %3;" : "=r"(d) : "r"(a), "r"(b), "r"(c)); return d; }
__device__ __forceinline__ uint32_t hadd2(uint32_t a, uint32_t b) { uint32_t d; asm("add.rn.bf16x2 %0, %1, %2;" : "=r"(d) : "r"(a), "r"(b)); return d; }
__device__ __forceinline__ uint32_t opaque(uint32_t v) { uint32_t r; asm volatile("mov.b32 %0, %1;" : "=r"(r) : "r"(v)); return r; }
__device__ __forceinline__ void ldsm4(uint32_t (&r)[4], uint32_t a) {
  asm volatile("ldmatrix.sync.aligned.m8n8.x4.shared.b16 {%0,%1,%2,%3}, [%4];" : "=r"(r[0]), "=r"(r[1]), "=r"(r[2]), "=r"(r[3]) : "r"(a));
}
__device__ __forceinline__ uint4 lds128(uint32_t a) { uint4 v; asm volatile("ld.shared.v4.b32 {%0,%1,%2,%3}, [%4];" : "=r"(v.x), "=r"(v.y), "=r"(v.z), "=r"(v.w) : "r"(a)); return v; }
__device__ __forceinline__ void sts128(uint32_t a, uint4 v) { asm volatile("st.shared.v4.b32 [%0], {%1,%2,%3,%4};" :: "r"(a), "r"(v.x), "r"(v.y), "r"(v.z), "r"(v.w) : "memory"); }
__device__ __forceinline__ uint32_t lds32(uint32_t a) { uint32_t v; asm volatile("ld.shared.b32 %0, [%1];" : "=r"(v) : "r"(a)); return v; }
__device__ __forceinline__ void sts32(uint32_t a, uint32_t v) { asm volatile("st.shared.b32 [%0], %1;" :: "r"(a), "r"(v) : "memory"); }
template <int R> __device__ __forceinline__ void reg_inc() { asm volatile("setmaxnreg.inc.sync.aligned.u32 %0;" :: "n"(R)); }
template <int R> __device__ __forceinline__ void reg_dec() { asm volatile("setmaxnreg.dec.sync.aligned.u32 %0;" :: "n"(R)); }

__device__ __forceinline__ unsigned int epoch_arrive(unsigned int* cnt, unsigned int n) {
  unsigned int old;
  asm volatile("atom.add.release.gpu.global.u32 %0, [%1], 1;" : "=r"(old) : "l"(cnt) : "memory");
  return (old / n + 1) * n;
}
__device__ __forceinline__ void epoch_wait(unsigned int* cnt, unsigned int target) {
  for (int it = 0; it < (1 << 22); it++) {
    unsigned int v;
    asm volatile("ld.acquire.gpu.global.u32 %0, [%1];" : "=r"(v) : "l"(cnt) : "memory");
    if ((int)(v - target) >= 0) break;
  }
}

#define TL(k, i)
#define TLT(k, i, t)
#define TLC(k, i, t)

__device__ __forceinline__ void wgmma_rs_n216_tb(float (&d)[108], uint32_t a0, uint32_t a1, uint32_t a2, uint32_t a3, uint64_t db, int sd) {
  asm volatile("{\n.reg .pred p;\nsetp.ne.b32 p, %113, 0;\n"
    "wgmma.mma_async.sync.aligned.m64n216k16.f32.bf16.bf16 "
    "{%0, %1, %2, %3, %4, %5, %6, %7, %8, %9, %10, %11, %12, %13, %14, %15, %16, %17, %18, %19, %20, %21, %22, %23, %24, %25, %26, %27, %28, %29, %30, %31, %32, %33, %34, %35, %36, %37, %38, %39, %40, %41, %42, %43, %44, %45, %46, %47, %48, %49, %50, %51, %52, %53, %54, %55, %56, %57, %58, %59, %60, %61, %62, %63, %64, %65, %66, %67, %68, %69, %70, %71, %72, %73, %74, %75, %76, %77, %78, %79, %80, %81, %82, %83, %84, %85, %86, %87, %88, %89, %90, %91, %92, %93, %94, %95, %96, %97, %98, %99, %100, %101, %102, %103, %104, %105, %106, %107}, {%108,%109,%110,%111}, %112, p, 1, 1, 1;\n}\n"
    : "+f"(d[0]), "+f"(d[1]), "+f"(d[2]), "+f"(d[3]), "+f"(d[4]), "+f"(d[5]), "+f"(d[6]), "+f"(d[7]), "+f"(d[8]), "+f"(d[9]), "+f"(d[10]), "+f"(d[11]), "+f"(d[12]), "+f"(d[13]), "+f"(d[14]), "+f"(d[15]), "+f"(d[16]), "+f"(d[17]), "+f"(d[18]), "+f"(d[19]), "+f"(d[20]), "+f"(d[21]), "+f"(d[22]), "+f"(d[23]), "+f"(d[24]), "+f"(d[25]), "+f"(d[26]), "+f"(d[27]), "+f"(d[28]), "+f"(d[29]), "+f"(d[30]), "+f"(d[31]), "+f"(d[32]), "+f"(d[33]), "+f"(d[34]), "+f"(d[35]), "+f"(d[36]), "+f"(d[37]), "+f"(d[38]), "+f"(d[39]), "+f"(d[40]), "+f"(d[41]), "+f"(d[42]), "+f"(d[43]), "+f"(d[44]), "+f"(d[45]), "+f"(d[46]), "+f"(d[47]), "+f"(d[48]), "+f"(d[49]), "+f"(d[50]), "+f"(d[51]), "+f"(d[52]), "+f"(d[53]), "+f"(d[54]), "+f"(d[55]), "+f"(d[56]), "+f"(d[57]), "+f"(d[58]), "+f"(d[59]), "+f"(d[60]), "+f"(d[61]), "+f"(d[62]), "+f"(d[63]), "+f"(d[64]), "+f"(d[65]), "+f"(d[66]), "+f"(d[67]), "+f"(d[68]), "+f"(d[69]), "+f"(d[70]), "+f"(d[71]), "+f"(d[72]), "+f"(d[73]), "+f"(d[74]), "+f"(d[75]), "+f"(d[76]), "+f"(d[77]), "+f"(d[78]), "+f"(d[79]), "+f"(d[80]), "+f"(d[81]), "+f"(d[82]), "+f"(d[83]), "+f"(d[84]), "+f"(d[85]), "+f"(d[86]), "+f"(d[87]), "+f"(d[88]), "+f"(d[89]), "+f"(d[90]), "+f"(d[91]), "+f"(d[92]), "+f"(d[93]), "+f"(d[94]), "+f"(d[95]), "+f"(d[96]), "+f"(d[97]), "+f"(d[98]), "+f"(d[99]), "+f"(d[100]), "+f"(d[101]), "+f"(d[102]), "+f"(d[103]), "+f"(d[104]), "+f"(d[105]), "+f"(d[106]), "+f"(d[107])
    : "r"(a0), "r"(a1), "r"(a2), "r"(a3), "l"(db), "r"(sd));
}
__device__ __forceinline__ void wgmma_ss_n72_tb(float (&d)[36], uint64_t da, uint64_t db, int sd) {
  asm volatile("{\n.reg .pred p;\nsetp.ne.b32 p, %38, 0;\n"
    "wgmma.mma_async.sync.aligned.m64n72k16.f32.bf16.bf16 "
    "{%0, %1, %2, %3, %4, %5, %6, %7, %8, %9, %10, %11, %12, %13, %14, %15, %16, %17, %18, %19, %20, %21, %22, %23, %24, %25, %26, %27, %28, %29, %30, %31, %32, %33, %34, %35}, %36, %37, p, 1, 1, 0, 1;\n}\n"
    : "+f"(d[0]), "+f"(d[1]), "+f"(d[2]), "+f"(d[3]), "+f"(d[4]), "+f"(d[5]), "+f"(d[6]), "+f"(d[7]), "+f"(d[8]), "+f"(d[9]), "+f"(d[10]), "+f"(d[11]), "+f"(d[12]), "+f"(d[13]), "+f"(d[14]), "+f"(d[15]), "+f"(d[16]), "+f"(d[17]), "+f"(d[18]), "+f"(d[19]), "+f"(d[20]), "+f"(d[21]), "+f"(d[22]), "+f"(d[23]), "+f"(d[24]), "+f"(d[25]), "+f"(d[26]), "+f"(d[27]), "+f"(d[28]), "+f"(d[29]), "+f"(d[30]), "+f"(d[31]), "+f"(d[32]), "+f"(d[33]), "+f"(d[34]), "+f"(d[35])
    : "l"(da), "l"(db), "r"(sd));
}
__device__ __forceinline__ void wgmma_ss_n192_tb(float (&d)[96], uint64_t da, uint64_t db, int sd) {
  asm volatile("{\n.reg .pred p;\nsetp.ne.b32 p, %98, 0;\n"
    "wgmma.mma_async.sync.aligned.m64n192k16.f32.bf16.bf16 "
    "{%0, %1, %2, %3, %4, %5, %6, %7, %8, %9, %10, %11, %12, %13, %14, %15, %16, %17, %18, %19, %20, %21, %22, %23, %24, %25, %26, %27, %28, %29, %30, %31, %32, %33, %34, %35, %36, %37, %38, %39, %40, %41, %42, %43, %44, %45, %46, %47, %48, %49, %50, %51, %52, %53, %54, %55, %56, %57, %58, %59, %60, %61, %62, %63, %64, %65, %66, %67, %68, %69, %70, %71, %72, %73, %74, %75, %76, %77, %78, %79, %80, %81, %82, %83, %84, %85, %86, %87, %88, %89, %90, %91, %92, %93, %94, %95}, %96, %97, p, 1, 1, 0, 1;\n}\n"
    : "+f"(d[0]), "+f"(d[1]), "+f"(d[2]), "+f"(d[3]), "+f"(d[4]), "+f"(d[5]), "+f"(d[6]), "+f"(d[7]), "+f"(d[8]), "+f"(d[9]), "+f"(d[10]), "+f"(d[11]), "+f"(d[12]), "+f"(d[13]), "+f"(d[14]), "+f"(d[15]), "+f"(d[16]), "+f"(d[17]), "+f"(d[18]), "+f"(d[19]), "+f"(d[20]), "+f"(d[21]), "+f"(d[22]), "+f"(d[23]), "+f"(d[24]), "+f"(d[25]), "+f"(d[26]), "+f"(d[27]), "+f"(d[28]), "+f"(d[29]), "+f"(d[30]), "+f"(d[31]), "+f"(d[32]), "+f"(d[33]), "+f"(d[34]), "+f"(d[35]), "+f"(d[36]), "+f"(d[37]), "+f"(d[38]), "+f"(d[39]), "+f"(d[40]), "+f"(d[41]), "+f"(d[42]), "+f"(d[43]), "+f"(d[44]), "+f"(d[45]), "+f"(d[46]), "+f"(d[47]), "+f"(d[48]), "+f"(d[49]), "+f"(d[50]), "+f"(d[51]), "+f"(d[52]), "+f"(d[53]), "+f"(d[54]), "+f"(d[55]), "+f"(d[56]), "+f"(d[57]), "+f"(d[58]), "+f"(d[59]), "+f"(d[60]), "+f"(d[61]), "+f"(d[62]), "+f"(d[63]), "+f"(d[64]), "+f"(d[65]), "+f"(d[66]), "+f"(d[67]), "+f"(d[68]), "+f"(d[69]), "+f"(d[70]), "+f"(d[71]), "+f"(d[72]), "+f"(d[73]), "+f"(d[74]), "+f"(d[75]), "+f"(d[76]), "+f"(d[77]), "+f"(d[78]), "+f"(d[79]), "+f"(d[80]), "+f"(d[81]), "+f"(d[82]), "+f"(d[83]), "+f"(d[84]), "+f"(d[85]), "+f"(d[86]), "+f"(d[87]), "+f"(d[88]), "+f"(d[89]), "+f"(d[90]), "+f"(d[91]), "+f"(d[92]), "+f"(d[93]), "+f"(d[94]), "+f"(d[95])
    : "l"(da), "l"(db), "r"(sd));
}
__device__ __forceinline__ void wgmma_rs_n256_tb(float (&d)[128], uint32_t a0, uint32_t a1, uint32_t a2, uint32_t a3, uint64_t db, int sd) {
  asm volatile("{\n.reg .pred p;\nsetp.ne.b32 p, %133, 0;\n"
    "wgmma.mma_async.sync.aligned.m64n256k16.f32.bf16.bf16 "
    "{%0, %1, %2, %3, %4, %5, %6, %7, %8, %9, %10, %11, %12, %13, %14, %15, %16, %17, %18, %19, %20, %21, %22, %23, %24, %25, %26, %27, %28, %29, %30, %31, %32, %33, %34, %35, %36, %37, %38, %39, %40, %41, %42, %43, %44, %45, %46, %47, %48, %49, %50, %51, %52, %53, %54, %55, %56, %57, %58, %59, %60, %61, %62, %63, %64, %65, %66, %67, %68, %69, %70, %71, %72, %73, %74, %75, %76, %77, %78, %79, %80, %81, %82, %83, %84, %85, %86, %87, %88, %89, %90, %91, %92, %93, %94, %95, %96, %97, %98, %99, %100, %101, %102, %103, %104, %105, %106, %107, %108, %109, %110, %111, %112, %113, %114, %115, %116, %117, %118, %119, %120, %121, %122, %123, %124, %125, %126, %127}, {%128,%129,%130,%131}, %132, p, 1, 1, 1;\n}\n"
    : "+f"(d[0]), "+f"(d[1]), "+f"(d[2]), "+f"(d[3]), "+f"(d[4]), "+f"(d[5]), "+f"(d[6]), "+f"(d[7]), "+f"(d[8]), "+f"(d[9]), "+f"(d[10]), "+f"(d[11]), "+f"(d[12]), "+f"(d[13]), "+f"(d[14]), "+f"(d[15]), "+f"(d[16]), "+f"(d[17]), "+f"(d[18]), "+f"(d[19]), "+f"(d[20]), "+f"(d[21]), "+f"(d[22]), "+f"(d[23]), "+f"(d[24]), "+f"(d[25]), "+f"(d[26]), "+f"(d[27]), "+f"(d[28]), "+f"(d[29]), "+f"(d[30]), "+f"(d[31]), "+f"(d[32]), "+f"(d[33]), "+f"(d[34]), "+f"(d[35]), "+f"(d[36]), "+f"(d[37]), "+f"(d[38]), "+f"(d[39]), "+f"(d[40]), "+f"(d[41]), "+f"(d[42]), "+f"(d[43]), "+f"(d[44]), "+f"(d[45]), "+f"(d[46]), "+f"(d[47]), "+f"(d[48]), "+f"(d[49]), "+f"(d[50]), "+f"(d[51]), "+f"(d[52]), "+f"(d[53]), "+f"(d[54]), "+f"(d[55]), "+f"(d[56]), "+f"(d[57]), "+f"(d[58]), "+f"(d[59]), "+f"(d[60]), "+f"(d[61]), "+f"(d[62]), "+f"(d[63]), "+f"(d[64]), "+f"(d[65]), "+f"(d[66]), "+f"(d[67]), "+f"(d[68]), "+f"(d[69]), "+f"(d[70]), "+f"(d[71]), "+f"(d[72]), "+f"(d[73]), "+f"(d[74]), "+f"(d[75]), "+f"(d[76]), "+f"(d[77]), "+f"(d[78]), "+f"(d[79]), "+f"(d[80]), "+f"(d[81]), "+f"(d[82]), "+f"(d[83]), "+f"(d[84]), "+f"(d[85]), "+f"(d[86]), "+f"(d[87]), "+f"(d[88]), "+f"(d[89]), "+f"(d[90]), "+f"(d[91]), "+f"(d[92]), "+f"(d[93]), "+f"(d[94]), "+f"(d[95]), "+f"(d[96]), "+f"(d[97]), "+f"(d[98]), "+f"(d[99]), "+f"(d[100]), "+f"(d[101]), "+f"(d[102]), "+f"(d[103]), "+f"(d[104]), "+f"(d[105]), "+f"(d[106]), "+f"(d[107]), "+f"(d[108]), "+f"(d[109]), "+f"(d[110]), "+f"(d[111]), "+f"(d[112]), "+f"(d[113]), "+f"(d[114]), "+f"(d[115]), "+f"(d[116]), "+f"(d[117]), "+f"(d[118]), "+f"(d[119]), "+f"(d[120]), "+f"(d[121]), "+f"(d[122]), "+f"(d[123]), "+f"(d[124]), "+f"(d[125]), "+f"(d[126]), "+f"(d[127])
    : "r"(a0), "r"(a1), "r"(a2), "r"(a3), "l"(db), "r"(sd));
}
__device__ __forceinline__ void wgmma_rs_n32_tb(float (&d)[16], uint32_t a0, uint32_t a1, uint32_t a2, uint32_t a3, uint64_t db, int sd) {
  asm volatile("{\n.reg .pred p;\nsetp.ne.b32 p, %21, 0;\n"
    "wgmma.mma_async.sync.aligned.m64n32k16.f32.bf16.bf16 "
    "{%0, %1, %2, %3, %4, %5, %6, %7, %8, %9, %10, %11, %12, %13, %14, %15}, {%16,%17,%18,%19}, %20, p, 1, 1, 1;\n}\n"
    : "+f"(d[0]), "+f"(d[1]), "+f"(d[2]), "+f"(d[3]), "+f"(d[4]), "+f"(d[5]), "+f"(d[6]), "+f"(d[7]), "+f"(d[8]), "+f"(d[9]), "+f"(d[10]), "+f"(d[11]), "+f"(d[12]), "+f"(d[13]), "+f"(d[14]), "+f"(d[15])
    : "r"(a0), "r"(a1), "r"(a2), "r"(a3), "l"(db), "r"(sd));
}
__device__ __forceinline__ void wgmma_rs_n64(float (&d)[32], uint32_t a0, uint32_t a1, uint32_t a2, uint32_t a3, uint64_t db, int sd) {
  asm volatile("{\n.reg .pred p;\nsetp.ne.b32 p, %37, 0;\n"
    "wgmma.mma_async.sync.aligned.m64n64k16.f32.bf16.bf16 "
    "{%0, %1, %2, %3, %4, %5, %6, %7, %8, %9, %10, %11, %12, %13, %14, %15, %16, %17, %18, %19, %20, %21, %22, %23, %24, %25, %26, %27, %28, %29, %30, %31}, {%32,%33,%34,%35}, %36, p, 1, 1, 0;\n}\n"
    : "+f"(d[0]), "+f"(d[1]), "+f"(d[2]), "+f"(d[3]), "+f"(d[4]), "+f"(d[5]), "+f"(d[6]), "+f"(d[7]), "+f"(d[8]), "+f"(d[9]), "+f"(d[10]), "+f"(d[11]), "+f"(d[12]), "+f"(d[13]), "+f"(d[14]), "+f"(d[15]), "+f"(d[16]), "+f"(d[17]), "+f"(d[18]), "+f"(d[19]), "+f"(d[20]), "+f"(d[21]), "+f"(d[22]), "+f"(d[23]), "+f"(d[24]), "+f"(d[25]), "+f"(d[26]), "+f"(d[27]), "+f"(d[28]), "+f"(d[29]), "+f"(d[30]), "+f"(d[31])
    : "r"(a0), "r"(a1), "r"(a2), "r"(a3), "l"(db), "r"(sd));
}
__device__ __forceinline__ void wgmma_rs0_n64(float (&d)[32], uint32_t a0, uint32_t a1, uint32_t a2, uint32_t a3, uint64_t db) {
  asm volatile("{\n.reg .pred p;\nsetp.ne.b32 p, 0, 0;\n"
    "wgmma.mma_async.sync.aligned.m64n64k16.f32.bf16.bf16 "
    "{%0, %1, %2, %3, %4, %5, %6, %7, %8, %9, %10, %11, %12, %13, %14, %15, %16, %17, %18, %19, %20, %21, %22, %23, %24, %25, %26, %27, %28, %29, %30, %31}, {%32,%33,%34,%35}, %36, p, 1, 1, 0;\n}\n"
    : "=f"(d[0]), "=f"(d[1]), "=f"(d[2]), "=f"(d[3]), "=f"(d[4]), "=f"(d[5]), "=f"(d[6]), "=f"(d[7]), "=f"(d[8]), "=f"(d[9]), "=f"(d[10]), "=f"(d[11]), "=f"(d[12]), "=f"(d[13]), "=f"(d[14]), "=f"(d[15]), "=f"(d[16]), "=f"(d[17]), "=f"(d[18]), "=f"(d[19]), "=f"(d[20]), "=f"(d[21]), "=f"(d[22]), "=f"(d[23]), "=f"(d[24]), "=f"(d[25]), "=f"(d[26]), "=f"(d[27]), "=f"(d[28]), "=f"(d[29]), "=f"(d[30]), "=f"(d[31])
    : "r"(a0), "r"(a1), "r"(a2), "r"(a3), "l"(db));
}
__device__ __forceinline__ void wgmma_rs_n24_tb(float (&d)[12], uint32_t a0, uint32_t a1, uint32_t a2, uint32_t a3, uint64_t db, int sd) {
  asm volatile("{\n.reg .pred p;\nsetp.ne.b32 p, %17, 0;\n"
    "wgmma.mma_async.sync.aligned.m64n24k16.f32.bf16.bf16 "
    "{%0, %1, %2, %3, %4, %5, %6, %7, %8, %9, %10, %11}, {%12,%13,%14,%15}, %16, p, 1, 1, 1;\n}\n"
    : "+f"(d[0]), "+f"(d[1]), "+f"(d[2]), "+f"(d[3]), "+f"(d[4]), "+f"(d[5]), "+f"(d[6]), "+f"(d[7]), "+f"(d[8]), "+f"(d[9]), "+f"(d[10]), "+f"(d[11])
    : "r"(a0), "r"(a1), "r"(a2), "r"(a3), "l"(db), "r"(sd));
}

__device__ __forceinline__ float silu_ref(float c) { return bf_round(c / (1.0f + __expf(-c))); }

__global__ void __launch_bounds__(256) k0_mod_ln(const bf16* __restrict__ x, const bf16* __restrict__ c, const bf16* __restrict__ wmod) {
  __shared__ float red[8][32];
  TL(0, 0);
  pdl_launch();
  const int t = threadIdx.x, warp = t >> 5, lane = t & 31, b = blockIdx.x;
  const bool do_mod = b < 72;
  const int strip = b % 36, half = b / 36, cq = t & 3, kr = t >> 2;
  uint4 wv[5]; float cs[5];
  if (do_mod) {
#pragma unroll
    for (int j = 0; j < 5; j++) {
      const int kk = kr + 64 * j, k = half * 288 + kk;
      if (kk < 288) { wv[j] = __ldg(reinterpret_cast<const uint4*>(wmod + (size_t)k * (6 * DM) + strip * 32 + cq * 8)); cs[j] = __bfloat162float(c[k]); }
      else { wv[j] = make_uint4(0, 0, 0, 0); cs[j] = 0.f; }
    }
  }
  const int r0 = b * 16 + warp * 2;
  const uint32_t* xr = reinterpret_cast<const uint32_t*>(x + (size_t)r0 * DM);
  uint32_t xv[2][9];
#pragma unroll
  for (int j = 0; j < 9; j++) { xv[0][j] = __ldg(xr + lane + 32 * j); xv[1][j] = __ldg(xr + 288 + lane + 32 * j); }
  {
    float s0 = 0.f, s1 = 0.f;
#pragma unroll
    for (int j = 0; j < 9; j++) { s0 += bf_lo(xv[0][j]) + bf_hi(xv[0][j]); s1 += bf_lo(xv[1][j]) + bf_hi(xv[1][j]); }
#pragma unroll
    for (int o = 16; o; o >>= 1) { s0 += __shfl_xor_sync(0xffffffffu, s0, o); s1 += __shfl_xor_sync(0xffffffffu, s1, o); }
    const float m0 = s0 * (1.0f / DM), m1 = s1 * (1.0f / DM);
    float v0 = 0.f, v1 = 0.f;
#pragma unroll
    for (int j = 0; j < 9; j++) {
      float d;
      d = bf_lo(xv[0][j]) - m0; v0 = fmaf(d, d, v0); d = bf_hi(xv[0][j]) - m0; v0 = fmaf(d, d, v0);
      d = bf_lo(xv[1][j]) - m1; v1 = fmaf(d, d, v1); d = bf_hi(xv[1][j]) - m1; v1 = fmaf(d, d, v1);
    }
#pragma unroll
    for (int o = 16; o; o >>= 1) { v0 += __shfl_xor_sync(0xffffffffu, v0, o); v1 += __shfl_xor_sync(0xffffffffu, v1, o); }
    const float rs0 = 1.0f / sqrtf(v0 * (1.0f / DM) + 1e-5f), rs1 = 1.0f / sqrtf(v1 * (1.0f / DM) + 1e-5f);
    uint32_t* o32 = reinterpret_cast<uint32_t*>(g_xn + (size_t)r0 * DM);
#pragma unroll
    for (int j = 0; j < 9; j++) {
      o32[lane + 32 * j] = pack_bf16((bf_lo(xv[0][j]) - m0) * rs0, (bf_hi(xv[0][j]) - m0) * rs0);
      o32[288 + lane + 32 * j] = pack_bf16((bf_lo(xv[1][j]) - m1) * rs1, (bf_hi(xv[1][j]) - m1) * rs1);
    }
  }
  TL(0, 2);
  if (do_mod) {
    float acc[8];
#pragma unroll
    for (int i = 0; i < 8; i++) acc[i] = 0.f;
#pragma unroll
    for (int j = 0; j < 5; j++) {
      const float s = silu_ref(cs[j]);
      const uint32_t w[4] = {wv[j].x, wv[j].y, wv[j].z, wv[j].w};
#pragma unroll
      for (int i = 0; i < 4; i++) { acc[2 * i] = fmaf(s, bf_lo(w[i]), acc[2 * i]); acc[2 * i + 1] = fmaf(s, bf_hi(w[i]), acc[2 * i + 1]); }
    }
#pragma unroll
    for (int i = 0; i < 8; i++) {
#pragma unroll
      for (int o = 4; o < 32; o <<= 1) acc[i] += __shfl_xor_sync(0xffffffffu, acc[i], o);
    }
    if (lane < 4) {
#pragma unroll
      for (int i = 0; i < 8; i++) red[warp][lane * 8 + i] = acc[i];
    }
    __syncthreads();
    if (t < 32) {
      float s = 0.f;
#pragma unroll
      for (int w = 0; w < 8; w++) s += red[w][t];
      g_modp[half * 1152 + strip * 32 + t] = s;
    }
  }
  TL(0, 7);
}

__device__ __forceinline__ void mod_tail(const bf16* __restrict__ c, const bf16* __restrict__ wmod, int part, float* smf  ) {
  const int t = threadIdx.x;
  float* sc = smf;
  float* red = smf + 576;
  for (int k = t; k < DM; k += 512) sc[k] = silu_ref(__bfloat162float(c[k]));
  __syncthreads();
  const int cg = t % 72, rg = t / 72;
  float acc[8];
#pragma unroll
  for (int i = 0; i < 8; i++) acc[i] = 0.f;
  if (rg < 7) {
    const bf16* w = wmod + 1152 + part * 576 + cg * 8;
#pragma unroll 1
    for (int k0 = rg; k0 < DM; k0 += 7 * 12) {
      uint4 v[12];
#pragma unroll
      for (int j = 0; j < 12; j++) { const int k = k0 + 7 * j; v[j] = k < DM ? __ldg(reinterpret_cast<const uint4*>(w + (size_t)k * (6 * DM))) : make_uint4(0, 0, 0, 0); }
#pragma unroll
      for (int j = 0; j < 12; j++) {
        const int k = k0 + 7 * j;
        const float s = k < DM ? sc[k] : 0.f;
        acc[0] = fmaf(s, bf_lo(v[j].x), acc[0]); acc[1] = fmaf(s, bf_hi(v[j].x), acc[1]); acc[2] = fmaf(s, bf_lo(v[j].y), acc[2]); acc[3] = fmaf(s, bf_hi(v[j].y), acc[3]);
        acc[4] = fmaf(s, bf_lo(v[j].z), acc[4]); acc[5] = fmaf(s, bf_hi(v[j].z), acc[5]); acc[6] = fmaf(s, bf_lo(v[j].w), acc[6]); acc[7] = fmaf(s, bf_hi(v[j].w), acc[7]);
      }
    }
#pragma unroll
    for (int i = 0; i < 8; i++) red[rg * 576 + cg * 8 + i] = acc[i];
  }
  __syncthreads();
  for (int col = t; col < 576; col += 512) {
    float s = 0.f;
#pragma unroll
    for (int r = 0; r < 7; r++) s += red[r * 576 + col];
    g_mod[1152 + part * 576 + col] = __float2bfloat16_rn(s);
  }
}

constexpr int K1_NST = 5;
constexpr int K1_A = 0, K1_W = 147456, K1_MOD = K1_W + K1_NST * 16384, K1_RED = K1_MOD + 2304, K1_BAR = K1_RED + 256;
constexpr int K1_SMEM = K1_BAR + 8 * (9 + 2 * K1_NST);
#define QSCALE (0.23570226039551584f * 1.4426950408889634f)
__host__ __device__ constexpr bool poly_block(int b) {
  return b == 1 || b == 3 || b == 4 || b == 6 || b == 7;
}
constexpr uint32_t KPAD_POLY = 0x42FE47C0u;
constexpr uint32_t VPAD_ONE  = 0x00003F80u;

template <int ST>
__device__ __forceinline__ void k1_load_a(uint32_t (&A)[2][4], const uint32_t (&aoff)[4], uint32_t mtab) {
#pragma unroll
  for (int j = 0; j < 2; j++) {
    ldsm4(A[j], aoff[(ST & 1) * 2 + j] + (ST >> 1) * 16384);
    const uint4 m = lds128(mtab + (ST * 2 + j) * 64);
    A[j][0] = hfma2(A[j][0], m.x, m.z); A[j][1] = hfma2(A[j][1], m.x, m.z);
    A[j][2] = hfma2(A[j][2], m.y, m.w); A[j][3] = hfma2(A[j][3], m.y, m.w);
  }
}
template <int ST>
__device__ __forceinline__ void k1_steps(float (&acc)[108], uint32_t (&A)[3][2][4], const uint32_t (&aoff)[4], uint32_t mtab, uint64_t db0,
                                         uint32_t bx, uint32_t bwf, uint32_t rbe, bool releaser) {
  if constexpr (ST < 18) {
    constexpr int s = ST % K1_NST;
    mbar_wait(bwf + 8 * s, (ST / K1_NST) & 1);
    fence_regs(A[ST % 3][0]); fence_regs(A[ST % 3][1]);
    wg_fence();
#pragma unroll
    for (int j = 0; j < 2; j++)
      wgmma_rs_n216_tb(acc, A[ST % 3][j][0], A[ST % 3][j][1], A[ST % 3][j][2], A[ST % 3][j][3], db0 + (uint64_t)(s * 1024 + j * 128), 1);
    wg_commit();
    if constexpr (ST + 1 < 18) {
      if constexpr (((ST + 1) & 1) == 0) mbar_wait(bx + 8 * ((ST + 1) >> 1), 0);
      k1_load_a<ST + 1>(A[(ST + 1) % 3], aoff, mtab);
    }
    if constexpr (ST > 0) {
      wg_wait<1>();
      if (ST - 1 + K1_NST < 18 && releaser) mbar_arrive_remote(rbe + 8 * ((ST - 1) % K1_NST));
    }
    k1_steps<ST + 1>(acc, A, aoff, mtab, db0, bx, bwf, rbe, releaser);
  }
}

__global__ void __launch_bounds__(288, 1) k1_qkv(const __grid_constant__ CUtensorMap tm_xn, const __grid_constant__ CUtensorMap tm_w) {
  extern __shared__ __align__(1024) uint8_t smem[];
  const uint32_t sb = s2u(smem);
  const int tid = threadIdx.x, nt = (blockIdx.x >> 1) & 7, rb = (blockIdx.x >> 4) * 2 + (blockIdx.x & 1);
  const uint32_t bx = sb + K1_BAR, bwf = bx + 72, bwe = bwf + 8 * K1_NST;
  TL(1, 0);
  if (tid == 256) {
    for (int i = 0; i < 9; i++) mbar_init(bx + 8 * i, 1);
    for (int i = 0; i < K1_NST; i++) { mbar_init(bwf + 8 * i, 1); mbar_init(bwe + 8 * i, 4); }
    fence_barrier_init();
    tmap_prefetch(&tm_xn); tmap_prefetch(&tm_w);
  }
  __syncthreads();
  cluster_arrive_relaxed(); cluster_wait();
  pdl_launch();
  if (tid >= 256) {
    if (tid == 256) {
      const int rank = cluster_rank();
      auto load_w = [&](int st) {
        const int s = st % K1_NST;
        mbar_expect(bwf + 8 * s, 16384);
        for (int g = 2 * rank; g < 2 * rank + 2; g++) tma2d_mc(sb + K1_W + s * 16384 + g * 4096, &tm_w, nt * 216 + g * 64, st * 32, bwf + 8 * s);
      };
      auto load_x = [&](int c) { mbar_expect(bx + 8 * c, 16384); tma2d(sb + K1_A + c * 16384, &tm_xn, c * 64, rb * 128, bx + 8 * c); };
      load_w(0); load_w(1);
      if (rb < 8) for (int b = rb; b < 16 * 4; b += 8) tma2d_prefetch(&tm_w, nt * 216 + (b & 3) * 64, (2 + (b >> 2)) * 32);
      pdl_wait();
      load_x(0); load_w(2); load_x(1); load_w(3); load_w(4); load_x(2); load_x(3);
      for (int st = K1_NST; st < 18; st++) {
        mbar_wait(bwe + 8 * (st % K1_NST), (st / K1_NST - 1) & 1);
        load_w(st);
        if (st - K1_NST + 4 < 9) load_x(st - K1_NST + 4);
      }
      cluster_arrive_relaxed(); cluster_wait();
    }
    return;
  }
  const int wg = __reduce_max_sync(0xffffffffu, (unsigned)tid >> 7), wtid = tid & 127, warp = (tid >> 5) & 3, lane = tid & 31, g = lane >> 2, q4 = lane & 3;
  const uint32_t rbe = map_cta(bwe, wtid & 1);
  pdl_wait();
  TL(1, 1);
  {
    const float2* mp = reinterpret_cast<const float2*>(g_modp);
    for (int i = tid; i < 288; i += 256) {
      const float2 s0 = __ldcg(mp + i), s1 = __ldcg(mp + 576 + i), c0 = __ldcg(mp + 288 + i), c1 = __ldcg(mp + 576 + 288 + i);
      const uint32_t a = sb + K1_MOD + (i >> 3) * 64 + (i & 3) * 16 + ((i >> 2) & 1) * 4;
      sts32(a, hadd2(pack_bf16(c0.x + c1.x, c0.y + c1.y), 0x3F803F80u));
      sts32(a + 8, pack_bf16(s0.x + s1.x, s0.y + s1.y));
    }
  }
  bar_sync(1, 256);
  uint32_t aoff[4];
  {
    const int r = wg * 64 + warp * 16 + (lane & 7) + ((lane >> 3) & 1) * 8;
#pragma unroll
    for (int j = 0; j < 4; j++) aoff[j] = opaque(sb + K1_A + r * 128 + (((2 * j + (lane >> 4)) ^ (lane & 7)) << 4));
  }
  const uint32_t mtab = opaque(sb + K1_MOD + q4 * 16);
  float acc[108];
#pragma unroll
  for (int i = 0; i < 108; i++) acc[i] = 0.f;
  const uint64_t db0 = mkdesc(sb + K1_W, 4096, 1024, 1);
  uint32_t A[3][2][4];
  mbar_wait(bx, 0);
  TL(1, 5);
  k1_load_a<0>(A[0], aoff, mtab);
  k1_steps<0>(acc, A, aoff, mtab, db0, bx, bwf, rbe, wtid < 2);
  wg_wait<0>();
  fence_regs(acc);
  cluster_arrive_relaxed();
  TL(1, 2);
  bar_sync(1, 256);
  {
    const int tok = wg * 64 + warp * 16 + g;
    const uint32_t base = sb + (tok >> 3) * 384 + (tok & 7) * 16;
    int d = 2 * q4, sl = 0;
#pragma unroll
    for (int i = 0; i < 27; i++) {
      const float sc = (nt * 12 + sl < 32) ? QSCALE : 1.0f;
      const uint32_t a = base + sl * 6144 + (d >> 3) * 128 + (d & 7) * 2;
      sts32(a, pack_bf16(acc[4 * i] * sc, acc[4 * i + 1] * sc));
      sts32(a + 384, pack_bf16(acc[4 * i + 2] * sc, acc[4 * i + 3] * sc));
      d += 8;
      if (d >= 18) { d -= 18; sl++; }
    }
    const int tk = tid & 127;
#pragma unroll
    for (int i = 0; i < 6; i++) {
      const int s2 = (tid >> 7) + 2 * i, slot = nt * 12 + s2;
      uint32_t pad = 0;
      if (slot >= 64) pad = VPAD_ONE;
      else if (slot >= 32) pad = poly_block((tk >> 3) & 7) ? KPAD_POLY : 0u;
      const uint32_t a = sb + s2 * 6144 + (tk >> 3) * 384 + (tk & 7) * 16 + 256;
      sts32(a + 4, pad);
      asm volatile("st.shared.v2.b32 [%0], {%1, %1};" :: "r"(a + 8), "r"(0u) : "memory");
    }
  }
  fence_async_smem();
  bar_sync(1, 256);
  TL(1, 3);
  if (tid == 0) {
    for (int sl = 0; sl < 12; sl++)
      bulk_s2g(g_qkvp + (size_t)(nt * 12 + sl) * SLOT_BYTES + (size_t)rb * 6144, sb + sl * 6144, 6144);
    bulk_commit();
  }
  if (nt * 12 < 64) {
    const int tok = tid & 127;
    float* red = reinterpret_cast<float*>(smem + K1_RED);
#pragma unroll
    for (int i = 0; i < 6; i++) {
      const int sl = (tid >> 7) + 2 * i;
      const uint32_t a = sb + sl * 6144 + (tok >> 3) * 384 + (tok & 7) * 16;
      const uint4 v0 = lds128(a), v1 = lds128(a + 128);
      const uint32_t v2 = lds32(a + 256);
      float n2 = 0.f;
      const uint32_t w[9] = {v0.x, v0.y, v0.z, v0.w, v1.x, v1.y, v1.z, v1.w, v2};
#pragma unroll
      for (int j = 0; j < 9; j++) { n2 = fmaf(bf_lo(w[j]), bf_lo(w[j]), n2); n2 = fmaf(bf_hi(w[j]), bf_hi(w[j]), n2); }
      const uint32_t mx = __reduce_max_sync(0xffffffffu, __float_as_uint(n2) & 0x7FFFFFFFu);
      if (lane == 0) red[sl * 4 + warp] = __uint_as_float(mx);
    }
    bar_sync(1, 256);
    if (tid >= 32 && tid < 44) {
      const int sl = tid - 32, slot = nt * 12 + sl;
      const uint32_t* r = reinterpret_cast<const uint32_t*>(red) + sl * 4;
      if (slot < 64) g_nrm[slot * 16 + rb] = __uint_as_float(max(max(r[0], r[1]), max(r[2], r[3])));
    }
  }
  TL(1, 4);
  if (tid == 0) bulk_wait_all();
  TL(1, 7);
  cluster_wait();
}

constexpr int K2_K = 0, K2_V = SLOT_BYTES, K2_Q = 2 * SLOT_BYTES, K2_BAR = K2_Q + 512 * 48, K2_SMEM = K2_BAR + 8 * 19;
constexpr uint32_t EXP_C2 = 0x3EA93EA9u, EXP_C1 = 0x3B4E3B4Eu, EXP_C0 = 0x3F2C3F2Cu;
constexpr int K2_TD = 8 * 384 / 16;

__device__ __forceinline__ void attn_qk(float (&S)[32], const uint32_t (&q)[8], uint64_t kd) {
  wgmma_rs0_n64(S, q[0], q[1], q[2], q[3], kd);
  wgmma_rs_n64(S, q[4], q[5], q[6], q[7], kd + 16, 1);
}
__device__ __forceinline__ void attn_pv(float (&O)[12], const uint32_t (&P)[16], uint64_t vd) {
#pragma unroll
  for (int kk = 0; kk < 4; kk++) wgmma_rs_n24_tb(O, P[4 * kk], P[4 * kk + 1], P[4 * kk + 2], P[4 * kk + 3], vd + kk * 48, 1);
}
__device__ __forceinline__ void attn_exp(float (&S)[32], uint32_t c2, uint32_t cone) {
#pragma unroll
  for (int b = 0; b < 8; b++) {
    if (poly_block(b)) {
#pragma unroll
      for (int h = 0; h < 2; h++) {
        uint32_t w, y;
        asm("prmt.b32 %0, %1, %2, 0x5410;" : "=r"(w) : "r"(__float_as_uint(S[4 * b + 2 * h])), "r"(__float_as_uint(S[4 * b + 2 * h + 1])));
        asm("lop3.b32 %0, %1, 0x007F007F, %2, 0xEA;" : "=r"(y) : "r"(w), "r"(cone));
        const uint32_t p = hfma2(hfma2(y, c2, EXP_C1), y, EXP_C0);
        S[4 * b + 2 * h] = __uint_as_float(w);
        S[4 * b + 2 * h + 1] = __uint_as_float(p);
      }
    } else {
#pragma unroll
      for (int j = 0; j < 4; j++) S[4 * b + j] = ex2(S[4 * b + j]);
    }
  }
}
__device__ __forceinline__ void attn_pack(const float (&S)[32], uint32_t (&P)[16]) {
#pragma unroll
  for (int i = 0; i < 16; i++) {
    if (poly_block(i >> 1)) asm("lop3.b32 %0, %1, %2, 0xFF80FF80, 0xE4;" : "=r"(P[i]) : "r"(__float_as_uint(S[2 * i])), "r"(__float_as_uint(S[2 * i + 1])));
    else P[i] = pack_bf16(S[2 * i], S[2 * i + 1]);
  }
}

template <bool WAIT>
__device__ __forceinline__ void attn_fast_pass(float (&O)[12], const uint32_t (&q)[8], uint64_t kd, uint64_t vd, uint32_t bar) {
  float S[32]; uint32_t P[16];
  const uint32_t c2 = opaque(EXP_C2), cone = opaque(0x3F803F80u);
  if (WAIT) mbar_wait(bar, 0);
  wg_fence();
  attn_qk(S, q, kd);
  wg_commit();
  wg_wait<0>();
  fence_regs(S);
  attn_exp(S, c2, cone);
  attn_pack(S, P);
  auto step = [&]() {
    kd += K2_TD;
    fence_regs(P); fence_regs(O);
    wg_fence();
    attn_qk(S, q, kd);
    wg_commit();
    attn_pv(O, P, vd);
    wg_commit();
    vd += K2_TD;
    wg_wait<1>();
    fence_regs(S);
    attn_exp(S, c2, cone);
    fence_regs(S);
    wg_wait<0>();
    fence_regs(S); fence_regs(O);
    attn_pack(S, P);
  };
#pragma unroll 1
  for (int c = 1; c < 16; c++) {
    step();
    if (WAIT) mbar_wait(bar + 8 * c, 0);
    step();
  }
  step();
  fence_regs(P); fence_regs(O);
  wg_fence();
  attn_pv(O, P, vd);
  wg_commit();
  wg_wait<0>();
  fence_regs(O);
}

__device__ __forceinline__ void attn_safe_pass(float (&O)[12], const uint32_t (&q)[8], uint64_t kd, uint64_t vd, uint32_t bar) {
  float S[32]; uint32_t P[16];
  float m0 = -INFINITY, m1 = -INFINITY;
#pragma unroll 1
  for (int j = 0; j < 32; j++) {
    if ((j & 1) == 0) mbar_wait(bar + 8 * (j >> 1), 0);
    wg_fence();
    attn_qk(S, q, kd);
    wg_commit();
    wg_wait<0>();
    fence_regs(S);
    float x0 = m0, x1 = m1;
#pragma unroll
    for (int b = 0; b < 8; b++) { x0 = fmaxf(x0, fmaxf(S[4 * b], S[4 * b + 1])); x1 = fmaxf(x1, fmaxf(S[4 * b + 2], S[4 * b + 3])); }
    x0 = fmaxf(x0, __shfl_xor_sync(0xffffffffu, x0, 1)); x0 = fmaxf(x0, __shfl_xor_sync(0xffffffffu, x0, 2));
    x1 = fmaxf(x1, __shfl_xor_sync(0xffffffffu, x1, 1)); x1 = fmaxf(x1, __shfl_xor_sync(0xffffffffu, x1, 2));
    const float a0 = ex2(m0 - x0), a1 = ex2(m1 - x1);
    m0 = x0; m1 = x1;
#pragma unroll
    for (int b = 0; b < 3; b++) { O[4 * b] *= a0; O[4 * b + 1] *= a0; O[4 * b + 2] *= a1; O[4 * b + 3] *= a1; }
#pragma unroll
    for (int b = 0; b < 8; b++) {
      P[2 * b] = pack_bf16(ex2(S[4 * b] - m0), ex2(S[4 * b + 1] - m0));
      P[2 * b + 1] = pack_bf16(ex2(S[4 * b + 2] - m1), ex2(S[4 * b + 3] - m1));
    }
    fence_regs(P); fence_regs(O);
    wg_fence();
    attn_pv(O, P, vd);
    wg_commit();
    wg_wait<0>();
    fence_regs(O);
    kd += K2_TD; vd += K2_TD;
  }
}

__global__ void __launch_bounds__(512, 1) k2_attn(const bf16* __restrict__ cvec, const bf16* __restrict__ wmod, const bf16* __restrict__ wo,
                                                   const bf16* __restrict__ w1, const bf16* __restrict__ w2) {
  extern __shared__ __align__(1024) uint8_t smem[];
  const uint32_t sb = s2u(smem);
  const int head = blockIdx.x >> 2, qg = blockIdx.x & 3;
  const int tid = threadIdx.x, wg = __reduce_max_sync(0xffffffffu, (unsigned)tid >> 7), warp = (tid >> 5) & 3, lane = tid & 31, g = lane >> 2, q4 = lane & 3;
  const uint32_t bar = sb + K2_BAR;
  TL(2, 0);
  if (tid == 0) {
    for (int i = 0; i < 18; i++) mbar_init(bar + 8 * i, 1);
    fence_barrier_init();
  }
  __syncthreads();
  pdl_launch();
  if (blockIdx.x >= 128) {
    mod_tail(cvec, wmod, blockIdx.x - 128, reinterpret_cast<float*>(smem));
    pdl_wait();
    return;
  }
  pdl_wait();
  TL(2, 3);
  if ((tid >> 5) == 1) {
    uint32_t nv = 0;
    if (lane < 16) nv = __float_as_uint(__ldcg(&g_nrm[(32 + head) * 16 + lane]));
    else if (lane < 20) nv = __float_as_uint(__ldcg(&g_nrm[head * 16 + qg * 4 + lane - 16]));
    const uint32_t km = __reduce_max_sync(0xffffffffu, lane < 16 ? nv : 0u), qm = __reduce_max_sync(0xffffffffu, lane < 16 ? 0u : nv);
    if (lane == 0) sts32(bar + 8 * 18, __uint_as_float(km) * __uint_as_float(qm) <= 4096.0f ? 1u : 0u);
  }
  {
    const uint8_t* Qg = g_qkvp + (size_t)head * SLOT_BYTES + (size_t)qg * 512 * 48;
    const uint8_t* Kg = g_qkvp + (size_t)(32 + head) * SLOT_BYTES;
    const uint8_t* Vg = g_qkvp + (size_t)(64 + head) * SLOT_BYTES;
    auto load_chunk = [&](int c) {
      mbar_expect(bar + 8 * c, 2 * 6144);
      bulk_g2s(sb + K2_K + c * 6144, Kg + c * 6144, 6144, bar + 8 * c);
      bulk_g2s(sb + K2_V + c * 6144, Vg + c * 6144, 6144, bar + 8 * c);
    };
    if (tid == 0) {
      mbar_expect(bar + 8 * 16, 4 * 3072);
      for (int w = 0; w < 4; w++) bulk_g2s(sb + K2_Q + w * 6144, Qg + w * 6144, 3072, bar + 8 * 16);
      load_chunk(0); load_chunk(1);
      TL(2, 5);
    }
    __syncthreads();
    const int wid = tid >> 5;
    if (lane == 0 && wid >= 2) load_chunk(wid);
    if (tid == 32) {
      mbar_expect(bar + 8 * 17, 4 * 3072);
      for (int w = 0; w < 4; w++) bulk_g2s(sb + K2_Q + w * 6144 + 3072, Qg + w * 6144 + 3072, 3072, bar + 8 * 17);
    }
    __syncwarp();
  }
  TL(2, 1);
  const bool fast = lds32(bar + 8 * 18) != 0;
  const uint64_t kd = mkdesc(sb + K2_K, 128, 384, 0);
  const uint64_t vd = mkdesc(sb + K2_V, 384, 128, 0);
#pragma unroll 1
  for (int it = 0; it < 2; it++) {
    const int qt = wg * 2 + it;
    mbar_wait(bar + 8 * (16 + it), 0);
    if (it == 0) TL(2, 4);
    uint32_t q[8];
    {
      const uint32_t base = sb + K2_Q + (qt * 8 + warp * 2) * 384 + g * 16 + q4 * 4;
#pragma unroll
      for (int j = 0; j < 3; j++) { q[2 * j] = lds32(base + j * 128); q[2 * j + 1] = lds32(base + 384 + j * 128); }
      if (fast && q4 == 1) { q[4] = 0x3F803F80u; q[5] = 0x3F803F80u; }
      q[6] = opaque(0u); q[7] = opaque(0u);
    }
    if (it == 1 && tid == 0) {
      const char* a = reinterpret_cast<const char*>(w1) + (size_t)blockIdx.x * (DM * FF * 2 / 128);
      const char* b = reinterpret_cast<const char*>(w2) + (size_t)blockIdx.x * (DM * FF * 2 / 128);
      const char* c = reinterpret_cast<const char*>(wo) + (size_t)blockIdx.x * (DM * DM * 2 / 128);
      asm volatile("cp.async.bulk.prefetch.L2.global [%0], %1;" :: "l"(c), "r"(DM * DM * 2 / 128) : "memory");
      asm volatile("cp.async.bulk.prefetch.L2.global [%0], %1;" :: "l"(a), "r"(DM * FF * 2 / 128) : "memory");
      asm volatile("cp.async.bulk.prefetch.L2.global [%0], %1;" :: "l"(b), "r"(DM * FF * 2 / 128) : "memory");
    }
    float O[12];
#pragma unroll
    for (int i = 0; i < 12; i++) O[i] = 0.f;
    if (fast) {
      if (it == 0) attn_fast_pass<true>(O, q, kd, vd, bar);
      else attn_fast_pass<false>(O, q, kd, vd, bar);
    } else {
      attn_safe_pass(O, q, kd, vd, bar);
    }
    const float l0 = __shfl_sync(0xffffffffu, O[8], (lane & ~3) | 1), l1 = __shfl_sync(0xffffffffu, O[10], (lane & ~3) | 1);
    const float r0 = __frcp_rn(l0), r1 = __frcp_rn(l1);
    const int row = qg * 512 + qt * 64 + warp * 16 + g;
    uint32_t* o0 = reinterpret_cast<uint32_t*>(g_o + (size_t)row * DM + head * DHEAD + q4 * 2);
    uint32_t* o1 = o0 + 8 * DM / 2;
    o0[0] = pack_bf16(O[0] * r0, O[1] * r0);  o1[0] = pack_bf16(O[2] * r1, O[3] * r1);
    o0[4] = pack_bf16(O[4] * r0, O[5] * r0);  o1[4] = pack_bf16(O[6] * r1, O[7] * r1);
    if (q4 == 0) { o0[8] = pack_bf16(O[8] * r0, O[9] * r0);  o1[8] = pack_bf16(O[10] * r1, O[11] * r1); }
  }
  TL(2, 7);
}

constexpr int K3_NST = 5;
constexpr int K3_W = 0, K3_A = 147456, K3_X = 0, K3_MOD = K3_A + K3_NST * 16384, K3_BAR = K3_MOD + 3 * 144 + 16;
constexpr int K3_SMEM = K3_BAR + 8 * (9 + 3 + 2 * K3_NST);

__global__ void __launch_bounds__(288, 1) k3_wo(const __grid_constant__ CUtensorMap tm_o, const __grid_constant__ CUtensorMap tm_wo,
                                                const __grid_constant__ CUtensorMap tm_x, const __grid_constant__ CUtensorMap tm_x2,
                                                const __grid_constant__ CUtensorMap tm_h2) {
  extern __shared__ __align__(1024) uint8_t smem[];
  const uint32_t sb = s2u(smem);
  const int tid = threadIdx.x, nt = blockIdx.x & 7, rb = blockIdx.x >> 3;
  const uint32_t bw = sb + K3_BAR, bxb = bw + 72, bxe = bxb + 8, bmd = bxe + 8, baf = bmd + 8, bae = baf + 8 * K3_NST;
  TL(3, 0);
  if (tid == 256) {
    for (int i = 0; i < 10; i++) mbar_init(bw + 8 * i, 1);
    mbar_init(bxe, 2); mbar_init(bmd, 1);
    for (int i = 0; i < K3_NST; i++) { mbar_init(baf + 8 * i, 1); mbar_init(bae + 8 * i, 4); }
    fence_barrier_init();
    tmap_prefetch(&tm_o); tmap_prefetch(&tm_wo); tmap_prefetch(&tm_x); tmap_prefetch(&tm_x2); tmap_prefetch(&tm_h2);
  }
  __syncthreads();
  cluster_arrive_relaxed(); cluster_wait();
  pdl_launch();
  if (tid >= 256) {
    if (tid == 256) {
      const int rank = cluster_rank();
      auto load_w = [&](int c) {
        mbar_expect(bw + 8 * c, 16384);
        for (int g = 0; g < 2; g++) tma2d(sb + K3_W + c * 16384 + g * 8192, &tm_wo, nt * 72 + g * 64, c * 64, bw + 8 * c);
      };
      auto load_o = [&](int c) {
        const int s = c % K3_NST;
        mbar_expect(baf + 8 * s, 16384);
        tma2d_mc(sb + K3_A + s * 16384 + rank * 8192, &tm_o, c * 64, rb * 128 + rank * 64, baf + 8 * s);
      };
      load_w(0); load_w(1);
      pdl_wait();
      for (int c = 0; c < K3_NST; c++) { load_o(c); load_w(c + 2); }
      load_w(7); load_w(8);
      mbar_expect(bmd, 3 * 144);
      for (int v = 0; v < 3; v++) bulk_g2s(sb + K3_MOD + v * 144, g_mod + (2 + v) * DM + nt * 72, 144, bmd);
      for (int c = K3_NST; c < 9; c++) { mbar_wait(bae + 8 * (c - K3_NST), 0); load_o(c); }
      mbar_wait(bxe, 0);
      mbar_expect(bxb, 18432); tma2d(sb + K3_X, &tm_x, nt * 72, rb * 128, bxb);
      cluster_arrive_relaxed(); cluster_wait();
    }
    return;
  }
  const int wg = __reduce_max_sync(0xffffffffu, (unsigned)tid >> 7), wtid = tid & 127, warp = (tid >> 5) & 3, lane = tid & 31, g = lane >> 2, q4 = lane & 3;
  const int lrow = wg * 64 + warp * 16 + g, row = rb * 128 + lrow;
  const uint32_t rbe = map_cta(bae, wtid & 1);
  pdl_wait();
  TL(3, 1);
  float acc[36];
#pragma unroll
  for (int i = 0; i < 36; i++) acc[i] = 0.f;
  const uint64_t da0 = mkdesc(sb + K3_A + wg * 8192, 16, 1024, 1);
  const uint64_t db0 = mkdesc(sb + K3_W, 8192, 1024, 1);
#pragma unroll 1
  for (int c = 0; c < 9; c++) {
    const int s = c % K3_NST;
    mbar_wait(bw + 8 * c, 0);
    mbar_wait(baf + 8 * s, (c / K3_NST) & 1);
    wg_fence();
#pragma unroll
    for (int j = 0; j < 4; j++) wgmma_ss_n72_tb(acc, da0 + (uint64_t)(s * 1024 + j * 2), db0 + (uint64_t)(c * 1024 + j * 128), 1);
    wg_commit();
    if (c > 0) {
      wg_wait<1>();
      if (c - 1 + K3_NST < 9 && wtid < 2) mbar_arrive_remote(rbe + 8 * (c - 1));
      if (c == 2 && wtid == 0) mbar_arrive(bxe);
    }
  }
  wg_wait<0>();
  fence_regs(acc);
  cluster_arrive_relaxed();
  TL(3, 2);
  mbar_wait(bmd, 0);
  mbar_wait(bxb, 0);
  const uint32_t xa = sb + K3_X + lrow * 144 + q4 * 4, ma = sb + K3_MOD + q4 * 4;
  float s0 = 0.f, s1 = 0.f;
#pragma unroll
  for (int i = 0; i < 9; i++) {
    const uint32_t x0 = lds32(xa + 16 * i), x1 = lds32(xa + 8 * 144 + 16 * i);
    const uint32_t ga = lds32(ma + 16 * i);
    const float g0 = bf_lo(ga), g1 = bf_hi(ga);
    const uint32_t p0 = pack_bf16(bf_lo(x0) + bf_round(g0 * bf_round(acc[4 * i])), bf_hi(x0) + bf_round(g1 * bf_round(acc[4 * i + 1])));
    const uint32_t p1 = pack_bf16(bf_lo(x1) + bf_round(g0 * bf_round(acc[4 * i + 2])), bf_hi(x1) + bf_round(g1 * bf_round(acc[4 * i + 3])));
    sts32(xa + 16 * i, p0); sts32(xa + 8 * 144 + 16 * i, p1);
    acc[4 * i] = bf_lo(p0); acc[4 * i + 1] = bf_hi(p0); acc[4 * i + 2] = bf_lo(p1); acc[4 * i + 3] = bf_hi(p1);
    s0 += acc[4 * i] + acc[4 * i + 1]; s1 += acc[4 * i + 2] + acc[4 * i + 3];
  }
  s0 += __shfl_xor_sync(0xffffffffu, s0, 1); s1 += __shfl_xor_sync(0xffffffffu, s1, 1);
  s0 += __shfl_xor_sync(0xffffffffu, s0, 2); s1 += __shfl_xor_sync(0xffffffffu, s1, 2);
  const float m0 = s0 * (1.0f / 72), m1 = s1 * (1.0f / 72);
  float v0 = 0.f, v1 = 0.f;
#pragma unroll
  for (int i = 0; i < 9; i++) {
    float d;
    d = acc[4 * i] - m0; v0 = fmaf(d, d, v0); d = acc[4 * i + 1] - m0; v0 = fmaf(d, d, v0);
    d = acc[4 * i + 2] - m1; v1 = fmaf(d, d, v1); d = acc[4 * i + 3] - m1; v1 = fmaf(d, d, v1);
  }
  v0 += __shfl_xor_sync(0xffffffffu, v0, 1); v1 += __shfl_xor_sync(0xffffffffu, v1, 1);
  v0 += __shfl_xor_sync(0xffffffffu, v0, 2); v1 += __shfl_xor_sync(0xffffffffu, v1, 2);
  if (q4 == 0) { __stcg(&g_stats[row * 8 + nt], make_float2(m0, v0)); __stcg(&g_stats[(row + 8) * 8 + nt], make_float2(m1, v1)); }
  fence_async_smem();
  bar_sync(1, 256);
  TL(3, 3);
  if (tid == 0) {
    const unsigned int target = epoch_arrive(&g_cnt[rb], 8);
    tma2d_store(&tm_x2, sb + K3_X, nt * 72, rb * 128); bulk_commit();
    epoch_wait(&g_cnt[rb], target);
  }
  bar_sync(1, 256);
  float mean0, mean1, rs0, rs1;
  {
    const float4 a = __ldcg(reinterpret_cast<const float4*>(g_stats + row * 8) + q4);
    const float4 b = __ldcg(reinterpret_cast<const float4*>(g_stats + (row + 8) * 8) + q4);
    float sa = a.x + a.z, sb_ = b.x + b.z;
    sa += __shfl_xor_sync(0xffffffffu, sa, 1); sb_ += __shfl_xor_sync(0xffffffffu, sb_, 1);
    sa += __shfl_xor_sync(0xffffffffu, sa, 2); sb_ += __shfl_xor_sync(0xffffffffu, sb_, 2);
    mean0 = sa * 0.125f; mean1 = sb_ * 0.125f;
    float ma = a.y + a.w + 72.f * ((a.x - mean0) * (a.x - mean0) + (a.z - mean0) * (a.z - mean0));
    float mb = b.y + b.w + 72.f * ((b.x - mean1) * (b.x - mean1) + (b.z - mean1) * (b.z - mean1));
    ma += __shfl_xor_sync(0xffffffffu, ma, 1); mb += __shfl_xor_sync(0xffffffffu, mb, 1);
    ma += __shfl_xor_sync(0xffffffffu, ma, 2); mb += __shfl_xor_sync(0xffffffffu, mb, 2);
    rs0 = 1.0f / sqrtf(ma * (1.0f / DM) + 1e-5f); rs1 = 1.0f / sqrtf(mb * (1.0f / DM) + 1e-5f);
  }
  {
    const uint32_t ha = sb + K3_A + lrow * 144 + q4 * 4;
#pragma unroll
    for (int i = 0; i < 9; i++) {
      const uint32_t c1p = hadd2(lds32(ma + 288 + 16 * i), 0x3F803F80u), sh = lds32(ma + 144 + 16 * i);
      sts32(ha + 16 * i, hfma2(hfma2(pack_bf16((acc[4 * i] - mean0) * rs0, (acc[4 * i + 1] - mean0) * rs0), c1p, sh), 0x3F003F00u, 0x80008000u));
      sts32(ha + 8 * 144 + 16 * i, hfma2(hfma2(pack_bf16((acc[4 * i + 2] - mean1) * rs1, (acc[4 * i + 3] - mean1) * rs1), c1p, sh), 0x3F003F00u, 0x80008000u));
    }
  }
  fence_async_smem();
  bar_sync(1, 256);
  if (tid == 0) { tma2d_store(&tm_h2, sb + K3_A, nt * 72, rb * 128); bulk_commit(); bulk_wait_all(); }
  TL(3, 7);
  cluster_wait();
}

#define K4_BK 64
#define K4_STAGGER 0
constexpr int K4_KS = K4_BK / 16;
constexpr int K4_SPT = 576 / K4_BK;
constexpr int K4_NST = 3 * 64 / K4_BK;
constexpr int K4_STB = K4_BK * 384;
constexpr int K4_A = 0, K4_B = 147456, K4_ST = K4_B + K4_NST * K4_STB, K4_BAR = K4_ST + 8192, K4_SMEM = K4_BAR + 8 * (9 + 2 * K4_NST) + 8;

__device__ __forceinline__ uint32_t silu2(uint32_t v, uint32_t m16, uint32_t mhi) {
  const float lo = __uint_as_float(v * m16), hi = __uint_as_float(v & mhi);
  return pack_bf16(fmaf(lo, tanh_fast(lo), lo), fmaf(hi, tanh_fast(hi), hi));
}
template <int P>
__device__ __forceinline__ void k4_epi(const uint32_t (&pk)[48], uint32_t go, bf16* hp) {
  const uint32_t m16 = go << 16, mhi = 0u - m16;
  constexpr int B = 8 * (P >> 1) + (P & 1);
  uint4 r;
  r.x = silu2(pk[B], m16, mhi); r.y = silu2(pk[B + 2], m16, mhi); r.z = silu2(pk[B + 4], m16, mhi); r.w = silu2(pk[B + 6], m16, mhi);
  asm volatile("st.global.v4.b32 [%0], {%1,%2,%3,%4};" :: "l"(hp + (P & 1) * 8 * FF + 32 * (P >> 1)), "r"(r.x), "r"(r.y), "r"(r.z), "r"(r.w) : "memory");
}
template <int P0, int N>
__device__ __forceinline__ void k4_epi_n(const uint32_t (&pk)[48], uint32_t go, bf16* hp) {
  if constexpr (N > 0) { k4_epi<P0>(pk, go, hp); k4_epi_n<P0 + 1, N - 1>(pk, go, hp); }
}
__host__ __device__ constexpr int k4_first(int i) { return K4_SPT == 9 ? (i * 12 + 8) / 9 : (i * 12 + 17) / 18; }

template <int T, int I>
__device__ __forceinline__ void k4_steps(float (&acc)[96], const uint32_t (&pk)[48], uint64_t da0, uint64_t db0, uint32_t ba, uint32_t bbf,
                                         uint32_t rbe, int wtid, bf16* hp) {
  if constexpr (I < K4_SPT) {
    constexpr int st = T * K4_SPT + I, s = st % K4_NST, k0 = I * K4_KS;
    if (T == 0 && (k0 & 3) == 0) mbar_wait(ba + 8 * (k0 >> 2), 0);
    mbar_wait(bbf + 8 * s, (st / K4_NST) & 1);
    wg_fence();
#pragma unroll
    for (int j = 0; j < K4_KS; j++)
      wgmma_ss_n192_tb(acc, da0 + (uint64_t)(((k0 + j) >> 2) * 1024 + ((k0 + j) & 3) * 2), db0 + (uint64_t)(s * (K4_STB / 16) + j * 128), (I | j) != 0);
    wg_commit();
    if (I > 0) {
      wg_wait<1>();
      if (st - 1 + K4_NST < 3 * K4_SPT && wtid < 2) mbar_arrive_remote(rbe + 8 * ((st - 1) % K4_NST));
    }
    if constexpr (T > 0 && k4_first(I + 1) > k4_first(I)) {
      const uint32_t go = mbar_try(ba, 0);
      k4_epi_n<k4_first(I), k4_first(I + 1) - k4_first(I)>(pk, go, hp);
    }
    k4_steps<T, I + 1>(acc, pk, da0, db0, ba, bbf, rbe, wtid, hp);
  }
}
template <int T>
__device__ __forceinline__ void k4_tile(float (&acc)[96], const uint32_t (&pk)[48], uint64_t da0, uint64_t db0, uint32_t ba, uint32_t bbf,
                                        uint32_t rbe, int wtid, bf16* hprev) {
  k4_steps<T, 0>(acc, pk, da0, db0, ba, bbf, rbe, wtid, hprev);
  wg_wait<0>();
  fence_regs(acc);
  if (T * K4_SPT + K4_SPT - 1 + K4_NST < 3 * K4_SPT && wtid < 2) mbar_arrive_remote(rbe + 8 * ((T * K4_SPT + K4_SPT - 1) % K4_NST));
}
__device__ __forceinline__ void k4_pack(const float (&acc)[96], uint32_t (&pk)[48]) {
#pragma unroll
  for (int i = 0; i < 48; i++) pk[i] = pack_bf16(acc[2 * i], acc[2 * i + 1]);
}

__global__ void __launch_bounds__(384, 1) k4_mlp1(const __grid_constant__ CUtensorMap tm_h2, const __grid_constant__ CUtensorMap tm_w1) {
  extern __shared__ __align__(1024) uint8_t smem[];
  const uint32_t sb = s2u(smem);
  const int tid = threadIdx.x, rb = blockIdx.x & 15, fs = blockIdx.x >> 4;
  const uint32_t ba = sb + K4_BAR, bbf = ba + 72, bbe = bbf + 8 * K4_NST;
  TL(4, 0);
  if (tid == 0) {
    for (int i = 0; i < 9; i++) mbar_init(ba + 8 * i, 1);
    for (int i = 0; i < K4_NST; i++) { mbar_init(bbf + 8 * i, 1); mbar_init(bbe + 8 * i, 4); }
    fence_barrier_init();
    tmap_prefetch(&tm_h2); tmap_prefetch(&tm_w1);
  }
  __syncthreads();
  cluster_arrive_relaxed(); cluster_wait();
  pdl_launch();
  const int rank = cluster_rank();
  if (tid < 128) {
    reg_dec<40>();
    if (tid == 0) {
      for (int st = 0; st < 3 * K4_SPT; st++) {
        const int s = st % K4_NST, t = st / K4_SPT, i = st % K4_SPT;
        if (st == K4_NST) {
          pdl_wait();
          for (int cc = 0; cc < 4; cc++) { mbar_expect(ba + 8 * cc, 16384); tma2d(sb + K4_A + cc * 16384, &tm_h2, cc * 64, rb * 128, ba + 8 * cc); }
        }
        if (st >= K4_NST) mbar_wait(bbe + 8 * s, (st / K4_NST - 1) & 1);
        mbar_expect(bbf + 8 * s, K4_STB);
        for (int g = 0; g < 3; g++)
          tma2d_mc(sb + K4_B + s * K4_STB + g * (K4_STB / 3) + rank * (K4_STB / 6), &tm_w1, fs * 576 + t * 192 + g * 64, i * K4_BK + rank * (K4_BK / 2), bbf + 8 * s);
        if (st >= K4_NST && (st * K4_BK) % 64 == 0 && st * K4_BK / 64 + 1 < 9) {
          const int cc = st * K4_BK / 64 + 1;
          mbar_expect(ba + 8 * cc, 16384); tma2d(sb + K4_A + cc * 16384, &tm_h2, cc * 64, rb * 128, ba + 8 * cc);
        }
      }
      cluster_arrive_relaxed(); cluster_wait();
    }
  } else {
    reg_inc<232>();
    const int wg = __reduce_max_sync(0xffffffffu, ((unsigned)tid >> 7) - 1), wtid = tid & 127, warp = (tid >> 5) & 3, lane = tid & 31;
    const uint64_t da0 = mkdesc(sb + K4_A + wg * 8192, 16, 1024, 1);
    const uint64_t db0 = mkdesc(sb + K4_B, K4_STB / 3, 1024, 1);
    const uint32_t rbe = map_cta(bbe, wtid & 1);
    bf16* hp = g_H + (size_t)(rb * 128 + wg * 64 + warp * 16 + (lane >> 2)) * FF + fs * 576 + (lane & 3) * 8;
    float acc[96]; uint32_t pk[48];
#pragma unroll
    for (int i = 0; i < 96; i++) acc[i] = 0.f;
    TLT(4, 1, 128); TLC(4, 3, 128);
    k4_tile<0>(acc, pk, da0, db0, ba, bbf, rbe, wtid, hp);
    k4_pack(acc, pk);
    k4_tile<1>(acc, pk, da0, db0, ba, bbf, rbe, wtid, hp);
    k4_pack(acc, pk);
    k4_tile<2>(acc, pk, da0, db0, ba, bbf, rbe, wtid, hp + 192);
    cluster_arrive_relaxed();
    TLT(4, 2, 128); TLC(4, 4, 128);
    k4_pack(acc, pk);
    k4_epi_n<0, 12>(pk, 1u, hp + 384);
    TLT(4, 7, 128);
    cluster_wait();
  }
}

constexpr int K5_NST = 4;
constexpr int K5_STAGE = 16384 + 36864;
constexpr int K5_GB = K5_NST * K5_STAGE, K5_BAR = K5_GB + 576, K5_SMEM = K5_BAR + 8 * (2 * K5_NST + 1);

template <int I> __device__ __forceinline__ float k5_acc(const float (&a)[128], const float (&b)[16]) { if constexpr (I < 128) return a[I]; else return b[I - 128]; }

template <int QD, int I>
__device__ __forceinline__ void k5_stage(const float (&a)[128], const float (&b)[16], uint32_t dst, uint32_t gbs) {
  if constexpr (I < 9) {
    constexpr int B = 9 * QD + I;
    const uint32_t gb = lds32(gbs + B * 16);
    const float g0 = bf_lo(gb), g1 = bf_hi(gb);
    sts32(dst + I * 16, pack_bf16(k5_acc<4 * B>(a, b) * g0, k5_acc<4 * B + 1>(a, b) * g1));
    sts32(dst + 8 * 144 + I * 16, pack_bf16(k5_acc<4 * B + 2>(a, b) * g0, k5_acc<4 * B + 3>(a, b) * g1));
    k5_stage<QD, I + 1>(a, b, dst, gbs);
  }
}
template <int QD>
__device__ __forceinline__ void k5_quarter(const float (&a)[128], const float (&b)[16], uint32_t sb, uint32_t dst, uint32_t gbs, int wg, int wtid,
                                           const CUtensorMap* tm, int col, int row) {
  k5_stage<QD, 0>(a, b, dst + QD * 18432, gbs);
  fence_async_smem();
  bar_sync(2 + wg, 128);
  if (wtid == 0) {
    asm volatile("cp.reduce.async.bulk.tensor.2d.global.shared::cta.add.tile.bulk_group [%0, {%2, %3}], [%1];"
                 :: "l"(tm), "r"(sb + QD * 18432 + wg * 9216), "r"(col + QD * 72), "r"(row) : "memory");
    bulk_commit();
  }
}

__global__ void __launch_bounds__(384, 1) k5_mlp2(const __grid_constant__ CUtensorMap tm_h, const __grid_constant__ CUtensorMap tm_w2,
                                                  const __grid_constant__ CUtensorMap tm_w2n, const __grid_constant__ CUtensorMap tm_out) {
  extern __shared__ __align__(1024) uint8_t smem[];
  const uint32_t sb = s2u(smem);
  const int tid = threadIdx.x, rb = blockIdx.x & 15, nh = (blockIdx.x >> 4) & 1, ks = blockIdx.x >> 5;
  const uint32_t bf = sb + K5_BAR, be = bf + 8 * K5_NST, bg = be + 8 * K5_NST;
  TL(5, 0);
  if (tid == 0) {
    for (int i = 0; i < K5_NST; i++) { mbar_init(bf + 8 * i, 1); mbar_init(be + 8 * i, 4); }
    mbar_init(bg, 1);
    fence_barrier_init();
    tmap_prefetch(&tm_h); tmap_prefetch(&tm_w2); tmap_prefetch(&tm_w2n); tmap_prefetch(&tm_out);
  }
  __syncthreads();
  cluster_arrive_relaxed(); cluster_wait();
  const int rank = cluster_rank();
  if (tid < 128) {
    reg_dec<40>();
    if (tid == 0) {
      auto load_b = [&](int st) {
        const int s = st % K5_NST;
        mbar_expect(bf + 8 * s, K5_STAGE);
        for (int g = 2 * rank; g < 2 * rank + 2; g++)
          tma5d_mc(sb + s * K5_STAGE + 16384 + g * 8192, &tm_w2, nh * 288 + g * 64, 0, 0, 0, (ks * 18 + st) * 2, bf + 8 * s);
        if (rank == 1) tma5d_mc(sb + s * K5_STAGE + 16384 + 32768, &tm_w2n, nh * 288 + 256, 0, 0, 0, (ks * 18 + st) * 2, bf + 8 * s);
      };
      load_b(0);
      pdl_wait();
      for (int st = 0; st < 18; st++) {
        const int s = st % K5_NST;
        if (st >= K5_NST) mbar_wait(be + 8 * s, (st / K5_NST - 1) & 1);
        if (st >= 1) load_b(st);
        tma2d(sb + s * K5_STAGE, &tm_h, (ks * 18 + st) * 64, rb * 128, bf + 8 * s);
        if (st == K5_NST) { mbar_expect(bg, 576); bulk_g2s(sb + K5_GB, g_mod + 5 * DM + nh * 288, 576, bg); }
      }
      cluster_arrive_relaxed(); cluster_wait();
    }
  } else {
    reg_inc<232>();
    const int ctid = tid - 128, wg = __reduce_max_sync(0xffffffffu, (unsigned)ctid >> 7), wtid = tid & 127, warp = (tid >> 5) & 3, lane = tid & 31, g = lane >> 2, q4 = lane & 3;
    float a[128], b[16];
#pragma unroll
    for (int i = 0; i < 128; i++) a[i] = 0.f;
#pragma unroll
    for (int i = 0; i < 16; i++) b[i] = 0.f;
    const uint64_t db0 = mkdesc(sb + 16384, 8192, 1024, 1);
    const uint64_t dn0 = mkdesc(sb + 16384 + 32768, 4096, 512, 2);
    const uint32_t rbe = map_cta(be, wtid & 1);
    uint32_t aoff[4];
    {
      const int r = wg * 64 + warp * 16 + (lane & 7) + ((lane >> 3) & 1) * 8;
#pragma unroll
      for (int j = 0; j < 4; j++) aoff[j] = sb + r * 128 + (((2 * j + (lane >> 4)) ^ (lane & 7)) << 4);
    }
    uint32_t A0[4][4], A1[4][4];
    auto step = [&](uint32_t (&A)[4][4], int st) {
      const int s = st % K5_NST;
      mbar_wait(bf + 8 * s, (st / K5_NST) & 1);
#pragma unroll
      for (int j = 0; j < 4; j++) ldsm4(A[j], aoff[j] + s * K5_STAGE);
      fence_regs(A[0]); fence_regs(A[1]); fence_regs(A[2]); fence_regs(A[3]);
      wg_fence();
#pragma unroll
      for (int j = 0; j < 4; j++) {
        wgmma_rs_n256_tb(a, A[j][0], A[j][1], A[j][2], A[j][3], db0 + (uint64_t)(s * (K5_STAGE / 16) + j * 128), 1);
        wgmma_rs_n32_tb(b, A[j][0], A[j][1], A[j][2], A[j][3], dn0 + (uint64_t)(s * (K5_STAGE / 16) + j * 64), 1);
      }
      wg_commit();
      if (st > 0) {
        wg_wait<1>();
        if (st - 1 + K5_NST < 18 && wtid < 2) mbar_arrive_remote(rbe + 8 * ((st - 1) % K5_NST));
      }
    };
#pragma unroll 1
    for (int st = 0; st < 18; st += 2) { step(A0, st); step(A1, st + 1); }
    wg_wait<0>();
    fence_regs(a); fence_regs(b);
    cluster_arrive_relaxed();
    TLT(5, 2, 128);
    mbar_wait(bg, 0);
    bar_sync(1, 256);
    const uint32_t dst = sb + (wg * 64 + warp * 16 + g) * 144 + q4 * 4, gbs = sb + K5_GB + q4 * 4;
    k5_quarter<0>(a, b, sb, dst, gbs, wg, wtid, &tm_out, nh * 288, rb * 128 + wg * 64);
    k5_quarter<1>(a, b, sb, dst, gbs, wg, wtid, &tm_out, nh * 288, rb * 128 + wg * 64);
    k5_quarter<2>(a, b, sb, dst, gbs, wg, wtid, &tm_out, nh * 288, rb * 128 + wg * 64);
    k5_quarter<3>(a, b, sb, dst, gbs, wg, wtid, &tm_out, nh * 288, rb * 128 + wg * 64);
    TLT(5, 3, 128);
    if (wtid == 0) bulk_wait_all();
    TLT(5, 7, 128);
    cluster_wait();
  }
}

}

typedef CUresult (*EncodeTiledFn)(CUtensorMap*, CUtensorMapDataType, cuuint32_t, void*, const cuuint64_t*, const cuuint64_t*, const cuuint32_t*,
                                  const cuuint32_t*, CUtensorMapInterleave, CUtensorMapSwizzle, CUtensorMapL2promotion, CUtensorMapFloatOOBfill);

static void make_map2d(EncodeTiledFn enc, CUtensorMap* m, const void* base, int cols, int rows, int box_cols, int box_rows, CUtensorMapSwizzle sw) {
  cuuint64_t dims[2] = {(cuuint64_t)cols, (cuuint64_t)rows};
  cuuint64_t strides[1] = {(cuuint64_t)cols * 2};
  cuuint32_t box[2] = {(cuuint32_t)box_cols, (cuuint32_t)box_rows};
  cuuint32_t es[2] = {1, 1};
  enc(m, CU_TENSOR_MAP_DATA_TYPE_BFLOAT16, 2, const_cast<void*>(base), dims, strides, box, es, CU_TENSOR_MAP_INTERLEAVE_NONE, sw,
      CU_TENSOR_MAP_L2_PROMOTION_L2_128B, CU_TENSOR_MAP_FLOAT_OOB_FILL_NONE);
}

template <typename... KArgs, typename... Args>
static void launch(void (*kern)(KArgs...), int grid, int block, int smem, bool pdl, int cluster, Args... args) {
  cudaLaunchConfig_t cfg = {};
  cfg.gridDim = dim3(grid); cfg.blockDim = dim3(block); cfg.dynamicSmemBytes = smem; cfg.stream = cudaStreamPerThread;
  cudaLaunchAttribute at[2];
  int n = 0;
  if (pdl) { at[n].id = cudaLaunchAttributeProgrammaticStreamSerialization; at[n].val.programmaticStreamSerializationAllowed = 1; n++; }
  if (cluster > 1) { at[n].id = cudaLaunchAttributeClusterDimension; at[n].val.clusterDim.x = cluster; at[n].val.clusterDim.y = 1; at[n].val.clusterDim.z = 1; n++; }
  cfg.attrs = at; cfg.numAttrs = n;
  cudaLaunchKernelEx(&cfg, kern, KArgs(args)...);
}

#define USE_PDL 1

extern "C" void kernel_launch(void* const* d_in, const int* in_sizes, int n_in, void* d_out, int out_size) {
  (void)in_sizes; (void)n_in; (void)out_size;
  const bf16* x    = (const bf16*)d_in[0];
  const bf16* wqkv = (const bf16*)d_in[1];
  const bf16* wo   = (const bf16*)d_in[2];
  const bf16* w1   = (const bf16*)d_in[4];
  const bf16* w2   = (const bf16*)d_in[5];
  const bf16* c    = (const bf16*)d_in[6];
  const bf16* wmod = (const bf16*)d_in[7];
  bf16* out = (bf16*)d_out;

  static EncodeTiledFn enc = nullptr;
  if (!enc) {
    void* fn = nullptr; cudaDriverEntryPointQueryResult qr;
    cudaGetDriverEntryPoint("cuTensorMapEncodeTiled", &fn, cudaEnableDefault, &qr);
    enc = (EncodeTiledFn)fn;
    cudaFuncSetAttribute(k1_qkv, cudaFuncAttributeMaxDynamicSharedMemorySize, K1_SMEM);
    cudaFuncSetAttribute(k2_attn, cudaFuncAttributeMaxDynamicSharedMemorySize, K2_SMEM);
    cudaFuncSetAttribute(k3_wo, cudaFuncAttributeMaxDynamicSharedMemorySize, K3_SMEM);
    cudaFuncSetAttribute(k4_mlp1, cudaFuncAttributeMaxDynamicSharedMemorySize, K4_SMEM);
    cudaFuncSetAttribute(k5_mlp2, cudaFuncAttributeMaxDynamicSharedMemorySize, K5_SMEM);
  }
  void *p_arena, *p_h2;
  cudaGetSymbolAddress(&p_arena, g_arena); cudaGetSymbolAddress(&p_h2, g_h2);
  void* p_xn = p_arena;
  void* p_o = (uint8_t*)p_arena + SEQ * DM * 2 + 96 * SLOT_BYTES;
  void* p_H = p_arena;
  CUtensorMap tm_xn, tm_wqkv, tm_o, tm_wo, tm_x, tm_x2s, tm_h2s, tm_h2, tm_w1, tm_H, tm_w2, tm_w2n, tm_out;
  make_map2d(enc, &tm_xn, p_xn, DM, SEQ, 64, 128, CU_TENSOR_MAP_SWIZZLE_128B);
  make_map2d(enc, &tm_wqkv, wqkv, 3 * DM, DM, 64, 32, CU_TENSOR_MAP_SWIZZLE_128B);
  make_map2d(enc, &tm_o, p_o, DM, SEQ, 64, 64, CU_TENSOR_MAP_SWIZZLE_128B);
  make_map2d(enc, &tm_x, x, DM, SEQ, 72, 128, CU_TENSOR_MAP_SWIZZLE_NONE);
  make_map2d(enc, &tm_x2s, out, DM, SEQ, 72, 128, CU_TENSOR_MAP_SWIZZLE_NONE);
  make_map2d(enc, &tm_out, out, DM, SEQ, 72, 64, CU_TENSOR_MAP_SWIZZLE_NONE);
  make_map2d(enc, &tm_h2s, p_h2, DM, SEQ, 72, 128, CU_TENSOR_MAP_SWIZZLE_NONE);
  make_map2d(enc, &tm_wo, wo, DM, DM, 64, 64, CU_TENSOR_MAP_SWIZZLE_128B);
  make_map2d(enc, &tm_h2, p_h2, DM, SEQ, 64, 128, CU_TENSOR_MAP_SWIZZLE_128B);
  make_map2d(enc, &tm_w1, w1, FF, DM, 64, K4_BK / 2, CU_TENSOR_MAP_SWIZZLE_128B);
  make_map2d(enc, &tm_H, p_H, FF, SEQ, 64, 128, CU_TENSOR_MAP_SWIZZLE_128B);
  for (int narrow = 0; narrow < 2; narrow++) {
    cuuint64_t dims[5] = {(cuuint64_t)DM, 2, 4, 4, (cuuint64_t)(FF / 32)};
    cuuint64_t strides[4] = {(cuuint64_t)DM * 2, (cuuint64_t)DM * 2 * 8, (cuuint64_t)DM * 2 * 2, (cuuint64_t)DM * 2 * 32};
    cuuint32_t box[5] = {narrow ? 32u : 64u, 2, 4, 4, 2};
    cuuint32_t es[5] = {1, 1, 1, 1, 1};
    enc(narrow ? &tm_w2n : &tm_w2, CU_TENSOR_MAP_DATA_TYPE_BFLOAT16, 5, const_cast<bf16*>(w2), dims, strides, box, es, CU_TENSOR_MAP_INTERLEAVE_NONE,
        narrow ? CU_TENSOR_MAP_SWIZZLE_64B : CU_TENSOR_MAP_SWIZZLE_128B, CU_TENSOR_MAP_L2_PROMOTION_L2_128B, CU_TENSOR_MAP_FLOAT_OOB_FILL_NONE);
  }
  launch(k0_mod_ln, 128, 256, 0, false, 1, x, c, wmod);
  launch(k1_qkv, 128, 288, K1_SMEM, USE_PDL, 2, tm_xn, tm_wqkv);
  launch(k2_attn, 132, 512, K2_SMEM, USE_PDL, 1, c, wmod, wo, w1, w2);
  launch(k3_wo, 128, 288, K3_SMEM, USE_PDL, 2, tm_o, tm_wo, tm_x, tm_x2s, tm_h2s);
  launch(k4_mlp1, 128, 384, K4_SMEM, USE_PDL, 2, tm_h2, tm_w1);
  launch(k5_mlp2, 128, 384, K5_SMEM, USE_PDL, 2, tm_H, tm_w2, tm_w2n, tm_out);
}
```

```cpp
#include <cuda_runtime.h>
#include <cuda_bf16.h>
#include <cuda.h>
#include <stdint.h>

namespace {

constexpr int SEQ = 2048, DM = 576, DHEAD = 18, FF = 4608;
constexpr int SLOT_BYTES = SEQ * 48;

typedef __nv_bfloat16 bf16;

__device__ __align__(1024) bf16    g_mod[6 * DM];
__device__ __align__(1024) float   g_modp[2 * 2 * DM];
constexpr int ACT_BYTES = SEQ * DM * 2;
__device__ __align__(1024) uint8_t g_arena[ACT_BYTES + SEQ * FF * 2];
#define g_qkvp (g_arena)
#define g_h2   (reinterpret_cast<bf16*>(g_arena))
#define g_xn   (reinterpret_cast<bf16*>(g_arena + 96 * SLOT_BYTES))
#define g_o    (reinterpret_cast<bf16*>(g_arena + 96 * SLOT_BYTES))
#define g_H    (reinterpret_cast<bf16*>(g_arena + ACT_BYTES))
__device__ __align__(1024) float   g_nrm[16 * 64];
__device__ __align__(1024) bf16    g_woT[DM * DM];
__device__ __align__(1024) uint4   g_stats[SEQ * 8];
__device__ unsigned int g_epoch;

__device__ __forceinline__ uint32_t s2u(const void* p) { return (uint32_t)__cvta_generic_to_shared(p); }
__device__ __forceinline__ void mbar_init(uint32_t b, uint32_t c) { asm volatile("mbarrier.init.shared::cta.b64 [%0], %1;" :: "r"(b), "r"(c) : "memory"); }
__device__ __forceinline__ void mbar_expect(uint32_t b, uint32_t bytes) { asm volatile("mbarrier.arrive.expect_tx.shared::cta.b64 _, [%0], %1;" :: "r"(b), "r"(bytes) : "memory"); }
__device__ __forceinline__ void mbar_arrive(uint32_t b) { asm volatile("mbarrier.arrive.shared::cta.b64 _, [%0];" :: "r"(b) : "memory"); }
__device__ __forceinline__ bool mbar_try(uint32_t b, uint32_t ph) {
  uint32_t ok;
  asm volatile("{\n.reg .pred p;\nmbarrier.try_wait.parity.shared::cta.b64 p, [%1], %2;\nselp.u32 %0, 1, 0, p;\n}" : "=r"(ok) : "r"(b), "r"(ph) : "memory");
  return ok != 0;
}
__device__ __forceinline__ void mbar_wait(uint32_t b, uint32_t ph) {
  if (!mbar_try(b, ph)) {
    for (int n = 0; n < (1 << 22); n++) if (mbar_try(b, ph)) break;
  }
}
__device__ __forceinline__ void fence_barrier_init() { asm volatile("fence.mbarrier_init.release.cluster;" ::: "memory"); }
__device__ __forceinline__ void fence_async_smem() { asm volatile("fence.proxy.async.shared::cta;" ::: "memory"); }
__device__ __forceinline__ void bar_sync(int id, int n) { asm volatile("bar.sync %0, %1;" :: "r"(id), "r"(n) : "memory"); }
__device__ __forceinline__ void pdl_wait() { asm volatile("griddepcontrol.wait;" ::: "memory"); }
__device__ __forceinline__ void pdl_launch() { asm volatile("griddepcontrol.launch_dependents;" ::: "memory"); }
__device__ __forceinline__ void bulk_g2s(uint32_t dst, const void* src, uint32_t bytes, uint32_t bar) {
  asm volatile("cp.async.bulk.shared::cluster.global.mbarrier::complete_tx::bytes [%0], [%1], %2, [%3];" :: "r"(dst), "l"(src), "r"(bytes), "r"(bar) : "memory");
}
__device__ __forceinline__ void bulk_s2g(void* dst, uint32_t src, uint32_t bytes) {
  asm volatile("cp.async.bulk.global.shared::cta.bulk_group [%0], [%1], %2;" :: "l"(dst), "r"(src), "r"(bytes) : "memory");
}
__device__ __forceinline__ void bulk_commit() { asm volatile("cp.async.bulk.commit_group;" ::: "memory"); }
__device__ __forceinline__ void bulk_wait_read() { asm volatile("cp.async.bulk.wait_group.read 0;" ::: "memory"); }
__device__ __forceinline__ void tma2d(uint32_t dst, const CUtensorMap* m, int x, int y, uint32_t bar) {
  asm volatile("cp.async.bulk.tensor.2d.shared::cluster.global.mbarrier::complete_tx::bytes [%0], [%1, {%3, %4}], [%2];"
               :: "r"(dst), "l"(m), "r"(bar), "r"(x), "r"(y) : "memory");
}
__device__ __forceinline__ void tma5d(uint32_t dst, const CUtensorMap* m, int c0, int c1, int c2, int c3, int c4, uint32_t bar) {
  asm volatile("cp.async.bulk.tensor.5d.shared::cluster.global.mbarrier::complete_tx::bytes [%0], [%1, {%3, %4, %5, %6, %7}], [%2];"
               :: "r"(dst), "l"(m), "r"(bar), "r"(c0), "r"(c1), "r"(c2), "r"(c3), "r"(c4) : "memory");
}
__device__ __forceinline__ void tma2d_mc(uint32_t dst, const CUtensorMap* m, int x, int y, uint32_t bar) {
  asm volatile("cp.async.bulk.tensor.2d.shared::cluster.global.mbarrier::complete_tx::bytes.multicast::cluster [%0], [%1, {%3, %4}], [%2], %5;"
               :: "r"(dst), "l"(m), "r"(bar), "r"(x), "r"(y), "h"((uint16_t)3) : "memory");
}
__device__ __forceinline__ void tma5d_mc(uint32_t dst, const CUtensorMap* m, int c0, int c1, int c2, int c3, int c4, uint32_t bar) {
  asm volatile("cp.async.bulk.tensor.5d.shared::cluster.global.mbarrier::complete_tx::bytes.multicast::cluster [%0], [%1, {%3, %4, %5, %6, %7}], [%2], %8;"
               :: "r"(dst), "l"(m), "r"(bar), "r"(c0), "r"(c1), "r"(c2), "r"(c3), "r"(c4), "h"((uint16_t)3) : "memory");
}
__device__ __forceinline__ void tma2d_store(const CUtensorMap* m, uint32_t src, int x, int y) {
  asm volatile("cp.async.bulk.tensor.2d.global.shared::cta.bulk_group [%0, {%2, %3}], [%1];" :: "l"(m), "r"(src), "r"(x), "r"(y) : "memory");
}
__device__ __forceinline__ uint32_t map_cta(uint32_t a, uint32_t cta) { uint32_t r; asm("mapa.shared::cluster.u32 %0, %1, %2;" : "=r"(r) : "r"(a), "r"(cta)); return r; }
__device__ __forceinline__ void mbar_arrive_remote(uint32_t ra) { asm volatile("mbarrier.arrive.shared::cluster.b64 _, [%0];" :: "r"(ra) : "memory"); }
__device__ __forceinline__ void cluster_arrive() { asm volatile("barrier.cluster.arrive.release;" ::: "memory"); }
__device__ __forceinline__ void cluster_arrive_relaxed() { asm volatile("barrier.cluster.arrive.relaxed;" ::: "memory"); }
__device__ __forceinline__ void cluster_wait() { asm volatile("barrier.cluster.wait.acquire;" ::: "memory"); }
__device__ __forceinline__ uint32_t cluster_rank() { uint32_t r; asm("mov.u32 %0, %%cluster_ctarank;" : "=r"(r)); return r; }
__device__ __forceinline__ void tma2d_prefetch(const CUtensorMap* m, int x, int y) {
  asm volatile("cp.async.bulk.prefetch.tensor.2d.L2.global [%0, {%1, %2}];" :: "l"(m), "r"(x), "r"(y) : "memory");
}
__device__ __forceinline__ void tmap_prefetch(const CUtensorMap* m) { asm volatile("prefetch.tensormap [%0];" :: "l"(m) : "memory"); }
__device__ __forceinline__ void wg_fence() { asm volatile("wgmma.fence.sync.aligned;" ::: "memory"); }
__device__ __forceinline__ void wg_commit() { asm volatile("wgmma.commit_group.sync.aligned;" ::: "memory"); }
template <int N> __device__ __forceinline__ void wg_wait() { asm volatile("wgmma.wait_group.sync.aligned %0;" :: "n"(N) : "memory"); }
__device__ __forceinline__ uint64_t mkdesc(uint32_t addr, uint32_t lbo, uint32_t sbo, int sw) {
  return (uint64_t)((addr & 0x3FFFF) >> 4) | ((uint64_t)(lbo >> 4) << 16) | ((uint64_t)(sbo >> 4) << 32) | ((uint64_t)sw << 62);
}
template <int N> __device__ __forceinline__ void fence_regs(float (&d)[N]) {
#pragma unroll
  for (int i = 0; i < N; i++) asm volatile("" : "+f"(d[i]) :: "memory");
}
template <int N> __device__ __forceinline__ void fence_regs(uint32_t (&d)[N]) {
#pragma unroll
  for (int i = 0; i < N; i++) asm volatile("" : "+r"(d[i]) :: "memory");
}
__device__ __forceinline__ float ex2(float x) { float y; asm("ex2.approx.ftz.f32 %0, %1;" : "=f"(y) : "f"(x)); return y; }
__device__ __forceinline__ float tanh_fast(float x) { float y; asm("tanh.approx.f32 %0, %1;" : "=f"(y) : "f"(x)); return y; }
__device__ __forceinline__ uint32_t pack_bf16(float lo, float hi) { uint32_t v; asm("cvt.rn.bf16x2.f32 %0, %1, %2;" : "=r"(v) : "f"(hi), "f"(lo)); return v; }
__device__ __forceinline__ float bf_lo(uint32_t v) { return __uint_as_float(v << 16); }
__device__ __forceinline__ float bf_hi(uint32_t v) { return __uint_as_float(v & 0xFFFF0000u); }
__device__ __forceinline__ float bf_round(float x) { return __bfloat162float(__float2bfloat16_rn(x)); }
__device__ __forceinline__ uint32_t hfma2(uint32_t a, uint32_t b, uint32_t c) { uint32_t d; asm("fma.rn.bf16x2 %0, %1, %2, %3;" : "=r"(d) : "r"(a), "r"(b), "r"(c)); return d; }
__device__ __forceinline__ uint32_t hadd2(uint32_t a, uint32_t b) { uint32_t d; asm("add.rn.bf16x2 %0, %1, %2;" : "=r"(d) : "r"(a), "r"(b)); return d; }
__device__ __forceinline__ uint32_t opaque(uint32_t v) { uint32_t r; asm volatile("mov.b32 %0, %1;" : "=r"(r) : "r"(v)); return r; }
__device__ __forceinline__ void ldsm4(uint32_t (&r)[4], uint32_t a) {
  asm volatile("ldmatrix.sync.aligned.m8n8.x4.shared.b16 {%0,%1,%2,%3}, [%4];" : "=r"(r[0]), "=r"(r[1]), "=r"(r[2]), "=r"(r[3]) : "r"(a));
}
__device__ __forceinline__ uint4 lds128(uint32_t a) { uint4 v; asm volatile("ld.shared.v4.b32 {%0,%1,%2,%3}, [%4];" : "=r"(v.x), "=r"(v.y), "=r"(v.z), "=r"(v.w) : "r"(a)); return v; }
__device__ __forceinline__ void sts128(uint32_t a, uint4 v) { asm volatile("st.shared.v4.b32 [%0], {%1,%2,%3,%4};" :: "r"(a), "r"(v.x), "r"(v.y), "r"(v.z), "r"(v.w) : "memory"); }
__device__ __forceinline__ uint32_t lds32(uint32_t a) { uint32_t v; asm volatile("ld.shared.b32 %0, [%1];" : "=r"(v) : "r"(a)); return v; }
__device__ __forceinline__ void sts32(uint32_t a, uint32_t v) { asm volatile("st.shared.b32 [%0], %1;" :: "r"(a), "r"(v) : "memory"); }
template <int R> __device__ __forceinline__ void reg_inc() { asm volatile("setmaxnreg.inc.sync.aligned.u32 %0;" :: "n"(R)); }
template <int R> __device__ __forceinline__ void reg_dec() { asm volatile("setmaxnreg.dec.sync.aligned.u32 %0;" :: "n"(R)); }

#define TL(k, i)
#define TLT(k, i, t)
#define TLC(k, i, t)

__device__ __forceinline__ void wgmma_rs_n216_tb(float (&d)[108], uint32_t a0, uint32_t a1, uint32_t a2, uint32_t a3, uint64_t db, int sd) {
  asm volatile("{\n.reg .pred p;\nsetp.ne.b32 p, %113, 0;\n"
    "wgmma.mma_async.sync.aligned.m64n216k16.f32.bf16.bf16 "
    "{%0, %1, %2, %3, %4, %5, %6, %7, %8, %9, %10, %11, %12, %13, %14, %15, %16, %17, %18, %19, %20, %21, %22, %23, %24, %25, %26, %27, %28, %29, %30, %31, %32, %33, %34, %35, %36, %37, %38, %39, %40, %41, %42, %43, %44, %45, %46, %47, %48, %49, %50, %51, %52, %53, %54, %55, %56, %57, %58, %59, %60, %61, %62, %63, %64, %65, %66, %67, %68, %69, %70, %71, %72, %73, %74, %75, %76, %77, %78, %79, %80, %81, %82, %83, %84, %85, %86, %87, %88, %89, %90, %91, %92, %93, %94, %95, %96, %97, %98, %99, %100, %101, %102, %103, %104, %105, %106, %107}, {%108,%109,%110,%111}, %112, p, 1, 1, 1;\n}\n"
    : "+f"(d[0]), "+f"(d[1]), "+f"(d[2]), "+f"(d[3]), "+f"(d[4]), "+f"(d[5]), "+f"(d[6]), "+f"(d[7]), "+f"(d[8]), "+f"(d[9]), "+f"(d[10]), "+f"(d[11]), "+f"(d[12]), "+f"(d[13]), "+f"(d[14]), "+f"(d[15]), "+f"(d[16]), "+f"(d[17]), "+f"(d[18]), "+f"(d[19]), "+f"(d[20]), "+f"(d[21]), "+f"(d[22]), "+f"(d[23]), "+f"(d[24]), "+f"(d[25]), "+f"(d[26]), "+f"(d[27]), "+f"(d[28]), "+f"(d[29]), "+f"(d[30]), "+f"(d[31]), "+f"(d[32]), "+f"(d[33]), "+f"(d[34]), "+f"(d[35]), "+f"(d[36]), "+f"(d[37]), "+f"(d[38]), "+f"(d[39]), "+f"(d[40]), "+f"(d[41]), "+f"(d[42]), "+f"(d[43]), "+f"(d[44]), "+f"(d[45]), "+f"(d[46]), "+f"(d[47]), "+f"(d[48]), "+f"(d[49]), "+f"(d[50]), "+f"(d[51]), "+f"(d[52]), "+f"(d[53]), "+f"(d[54]), "+f"(d[55]), "+f"(d[56]), "+f"(d[57]), "+f"(d[58]), "+f"(d[59]), "+f"(d[60]), "+f"(d[61]), "+f"(d[62]), "+f"(d[63]), "+f"(d[64]), "+f"(d[65]), "+f"(d[66]), "+f"(d[67]), "+f"(d[68]), "+f"(d[69]), "+f"(d[70]), "+f"(d[71]), "+f"(d[72]), "+f"(d[73]), "+f"(d[74]), "+f"(d[75]), "+f"(d[76]), "+f"(d[77]), "+f"(d[78]), "+f"(d[79]), "+f"(d[80]), "+f"(d[81]), "+f"(d[82]), "+f"(d[83]), "+f"(d[84]), "+f"(d[85]), "+f"(d[86]), "+f"(d[87]), "+f"(d[88]), "+f"(d[89]), "+f"(d[90]), "+f"(d[91]), "+f"(d[92]), "+f"(d[93]), "+f"(d[94]), "+f"(d[95]), "+f"(d[96]), "+f"(d[97]), "+f"(d[98]), "+f"(d[99]), "+f"(d[100]), "+f"(d[101]), "+f"(d[102]), "+f"(d[103]), "+f"(d[104]), "+f"(d[105]), "+f"(d[106]), "+f"(d[107])
    : "r"(a0), "r"(a1), "r"(a2), "r"(a3), "l"(db), "r"(sd));
}
__device__ __forceinline__ void wgmma_ss_n72(float (&d)[36], uint64_t da, uint64_t db, int sd) {
  asm volatile("{\n.reg .pred p;\nsetp.ne.b32 p, %38, 0;\n"
    "wgmma.mma_async.sync.aligned.m64n72k16.f32.bf16.bf16 "
    "{%0, %1, %2, %3, %4, %5, %6, %7, %8, %9, %10, %11, %12, %13, %14, %15, %16, %17, %18, %19, %20, %21, %22, %23, %24, %25, %26, %27, %28, %29, %30, %31, %32, %33, %34, %35}, %36, %37, p, 1, 1, 0, 0;\n}\n"
    : "+f"(d[0]), "+f"(d[1]), "+f"(d[2]), "+f"(d[3]), "+f"(d[4]), "+f"(d[5]), "+f"(d[6]), "+f"(d[7]), "+f"(d[8]), "+f"(d[9]), "+f"(d[10]), "+f"(d[11]), "+f"(d[12]), "+f"(d[13]), "+f"(d[14]), "+f"(d[15]), "+f"(d[16]), "+f"(d[17]), "+f"(d[18]), "+f"(d[19]), "+f"(d[20]), "+f"(d[21]), "+f"(d[22]), "+f"(d[23]), "+f"(d[24]), "+f"(d[25]), "+f"(d[26]), "+f"(d[27]), "+f"(d[28]), "+f"(d[29]), "+f"(d[30]), "+f"(d[31]), "+f"(d[32]), "+f"(d[33]), "+f"(d[34]), "+f"(d[35])
    : "l"(da), "l"(db), "r"(sd));
}
__device__ __forceinline__ void wgmma_ss_n192_tb(float (&d)[96], uint64_t da, uint64_t db, int sd) {
  asm volatile("{\n.reg .pred p;\nsetp.ne.b32 p, %98, 0;\n"
    "wgmma.mma_async.sync.aligned.m64n192k16.f32.bf16.bf16 "
    "{%0, %1, %2, %3, %4, %5, %6, %7, %8, %9, %10, %11, %12, %13, %14, %15, %16, %17, %18, %19, %20, %21, %22, %23, %24, %25, %26, %27, %28, %29, %30, %31, %32, %33, %34, %35, %36, %37, %38, %39, %40, %41, %42, %43, %44, %45, %46, %47, %48, %49, %50, %51, %52, %53, %54, %55, %56, %57, %58, %59, %60, %61, %62, %63, %64, %65, %66, %67, %68, %69, %70, %71, %72, %73, %74, %75, %76, %77, %78, %79, %80, %81, %82, %83, %84, %85, %86, %87, %88, %89, %90, %91, %92, %93, %94, %95}, %96, %97, p, 1, 1, 0, 1;\n}\n"
    : "+f"(d[0]), "+f"(d[1]), "+f"(d[2]), "+f"(d[3]), "+f"(d[4]), "+f"(d[5]), "+f"(d[6]), "+f"(d[7]), "+f"(d[8]), "+f"(d[9]), "+f"(d[10]), "+f"(d[11]), "+f"(d[12]), "+f"(d[13]), "+f"(d[14]), "+f"(d[15]), "+f"(d[16]), "+f"(d[17]), "+f"(d[18]), "+f"(d[19]), "+f"(d[20]), "+f"(d[21]), "+f"(d[22]), "+f"(d[23]), "+f"(d[24]), "+f"(d[25]), "+f"(d[26]), "+f"(d[27]), "+f"(d[28]), "+f"(d[29]), "+f"(d[30]), "+f"(d[31]), "+f"(d[32]), "+f"(d[33]), "+f"(d[34]), "+f"(d[35]), "+f"(d[36]), "+f"(d[37]), "+f"(d[38]), "+f"(d[39]), "+f"(d[40]), "+f"(d[41]), "+f"(d[42]), "+f"(d[43]), "+f"(d[44]), "+f"(d[45]), "+f"(d[46]), "+f"(d[47]), "+f"(d[48]), "+f"(d[49]), "+f"(d[50]), "+f"(d[51]), "+f"(d[52]), "+f"(d[53]), "+f"(d[54]), "+f"(d[55]), "+f"(d[56]), "+f"(d[57]), "+f"(d[58]), "+f"(d[59]), "+f"(d[60]), "+f"(d[61]), "+f"(d[62]), "+f"(d[63]), "+f"(d[64]), "+f"(d[65]), "+f"(d[66]), "+f"(d[67]), "+f"(d[68]), "+f"(d[69]), "+f"(d[70]), "+f"(d[71]), "+f"(d[72]), "+f"(d[73]), "+f"(d[74]), "+f"(d[75]), "+f"(d[76]), "+f"(d[77]), "+f"(d[78]), "+f"(d[79]), "+f"(d[80]), "+f"(d[81]), "+f"(d[82]), "+f"(d[83]), "+f"(d[84]), "+f"(d[85]), "+f"(d[86]), "+f"(d[87]), "+f"(d[88]), "+f"(d[89]), "+f"(d[90]), "+f"(d[91]), "+f"(d[92]), "+f"(d[93]), "+f"(d[94]), "+f"(d[95])
    : "l"(da), "l"(db), "r"(sd));
}
__device__ __forceinline__ void wgmma_rs_n256_tb(float (&d)[128], uint32_t a0, uint32_t a1, uint32_t a2, uint32_t a3, uint64_t db, int sd) {
  asm volatile("{\n.reg .pred p;\nsetp.ne.b32 p, %133, 0;\n"
    "wgmma.mma_async.sync.aligned.m64n256k16.f32.bf16.bf16 "
    "{%0, %1, %2, %3, %4, %5, %6, %7, %8, %9, %10, %11, %12, %13, %14, %15, %16, %17, %18, %19, %20, %21, %22, %23, %24, %25, %26, %27, %28, %29, %30, %31, %32, %33, %34, %35, %36, %37, %38, %39, %40, %41, %42, %43, %44, %45, %46, %47, %48, %49, %50, %51, %52, %53, %54, %55, %56, %57, %58, %59, %60, %61, %62, %63, %64, %65, %66, %67, %68, %69, %70, %71, %72, %73, %74, %75, %76, %77, %78, %79, %80, %81, %82, %83, %84, %85, %86, %87, %88, %89, %90, %91, %92, %93, %94, %95, %96, %97, %98, %99, %100, %101, %102, %103, %104, %105, %106, %107, %108, %109, %110, %111, %112, %113, %114, %115, %116, %117, %118, %119, %120, %121, %122, %123, %124, %125, %126, %127}, {%128,%129,%130,%131}, %132, p, 1, 1, 1;\n}\n"
    : "+f"(d[0]), "+f"(d[1]), "+f"(d[2]), "+f"(d[3]), "+f"(d[4]), "+f"(d[5]), "+f"(d[6]), "+f"(d[7]), "+f"(d[8]), "+f"(d[9]), "+f"(d[10]), "+f"(d[11]), "+f"(d[12]), "+f"(d[13]), "+f"(d[14]), "+f"(d[15]), "+f"(d[16]), "+f"(d[17]), "+f"(d[18]), "+f"(d[19]), "+f"(d[20]), "+f"(d[21]), "+f"(d[22]), "+f"(d[23]), "+f"(d[24]), "+f"(d[25]), "+f"(d[26]), "+f"(d[27]), "+f"(d[28]), "+f"(d[29]), "+f"(d[30]), "+f"(d[31]), "+f"(d[32]), "+f"(d[33]), "+f"(d[34]), "+f"(d[35]), "+f"(d[36]), "+f"(d[37]), "+f"(d[38]), "+f"(d[39]), "+f"(d[40]), "+f"(d[41]), "+f"(d[42]), "+f"(d[43]), "+f"(d[44]), "+f"(d[45]), "+f"(d[46]), "+f"(d[47]), "+f"(d[48]), "+f"(d[49]), "+f"(d[50]), "+f"(d[51]), "+f"(d[52]), "+f"(d[53]), "+f"(d[54]), "+f"(d[55]), "+f"(d[56]), "+f"(d[57]), "+f"(d[58]), "+f"(d[59]), "+f"(d[60]), "+f"(d[61]), "+f"(d[62]), "+f"(d[63]), "+f"(d[64]), "+f"(d[65]), "+f"(d[66]), "+f"(d[67]), "+f"(d[68]), "+f"(d[69]), "+f"(d[70]), "+f"(d[71]), "+f"(d[72]), "+f"(d[73]), "+f"(d[74]), "+f"(d[75]), "+f"(d[76]), "+f"(d[77]), "+f"(d[78]), "+f"(d[79]), "+f"(d[80]), "+f"(d[81]), "+f"(d[82]), "+f"(d[83]), "+f"(d[84]), "+f"(d[85]), "+f"(d[86]), "+f"(d[87]), "+f"(d[88]), "+f"(d[89]), "+f"(d[90]), "+f"(d[91]), "+f"(d[92]), "+f"(d[93]), "+f"(d[94]), "+f"(d[95]), "+f"(d[96]), "+f"(d[97]), "+f"(d[98]), "+f"(d[99]), "+f"(d[100]), "+f"(d[101]), "+f"(d[102]), "+f"(d[103]), "+f"(d[104]), "+f"(d[105]), "+f"(d[106]), "+f"(d[107]), "+f"(d[108]), "+f"(d[109]), "+f"(d[110]), "+f"(d[111]), "+f"(d[112]), "+f"(d[113]), "+f"(d[114]), "+f"(d[115]), "+f"(d[116]), "+f"(d[117]), "+f"(d[118]), "+f"(d[119]), "+f"(d[120]), "+f"(d[121]), "+f"(d[122]), "+f"(d[123]), "+f"(d[124]), "+f"(d[125]), "+f"(d[126]), "+f"(d[127])
    : "r"(a0), "r"(a1), "r"(a2), "r"(a3), "l"(db), "r"(sd));
}
__device__ __forceinline__ void wgmma_rs_n32_tb(float (&d)[16], uint32_t a0, uint32_t a1, uint32_t a2, uint32_t a3, uint64_t db, int sd) {
  asm volatile("{\n.reg .pred p;\nsetp.ne.b32 p, %21, 0;\n"
    "wgmma.mma_async.sync.aligned.m64n32k16.f32.bf16.bf16 "
    "{%0, %1, %2, %3, %4, %5, %6, %7, %8, %9, %10, %11, %12, %13, %14, %15}, {%16,%17,%18,%19}, %20, p, 1, 1, 1;\n}\n"
    : "+f"(d[0]), "+f"(d[1]), "+f"(d[2]), "+f"(d[3]), "+f"(d[4]), "+f"(d[5]), "+f"(d[6]), "+f"(d[7]), "+f"(d[8]), "+f"(d[9]), "+f"(d[10]), "+f"(d[11]), "+f"(d[12]), "+f"(d[13]), "+f"(d[14]), "+f"(d[15])
    : "r"(a0), "r"(a1), "r"(a2), "r"(a3), "l"(db), "r"(sd));
}
__device__ __forceinline__ void wgmma_rs_n64(float (&d)[32], uint32_t a0, uint32_t a1, uint32_t a2, uint32_t a3, uint64_t db, int sd) {
  asm volatile("{\n.reg .pred p;\nsetp.ne.b32 p, %37, 0;\n"
    "wgmma.mma_async.sync.aligned.m64n64k16.f32.bf16.bf16 "
    "{%0, %1, %2, %3, %4, %5, %6, %7, %8, %9, %10, %11, %12, %13, %14, %15, %16, %17, %18, %19, %20, %21, %22, %23, %24, %25, %26, %27, %28, %29, %30, %31}, {%32,%33,%34,%35}, %36, p, 1, 1, 0;\n}\n"
    : "+f"(d[0]), "+f"(d[1]), "+f"(d[2]), "+f"(d[3]), "+f"(d[4]), "+f"(d[5]), "+f"(d[6]), "+f"(d[7]), "+f"(d[8]), "+f"(d[9]), "+f"(d[10]), "+f"(d[11]), "+f"(d[12]), "+f"(d[13]), "+f"(d[14]), "+f"(d[15]), "+f"(d[16]), "+f"(d[17]), "+f"(d[18]), "+f"(d[19]), "+f"(d[20]), "+f"(d[21]), "+f"(d[22]), "+f"(d[23]), "+f"(d[24]), "+f"(d[25]), "+f"(d[26]), "+f"(d[27]), "+f"(d[28]), "+f"(d[29]), "+f"(d[30]), "+f"(d[31])
    : "r"(a0), "r"(a1), "r"(a2), "r"(a3), "l"(db), "r"(sd));
}
__device__ __forceinline__ void wgmma_rs0_n64(float (&d)[32], uint32_t a0, uint32_t a1, uint32_t a2, uint32_t a3, uint64_t db) {
  asm volatile("{\n.reg .pred p;\nsetp.ne.b32 p, 0, 0;\n"
    "wgmma.mma_async.sync.aligned.m64n64k16.f32.bf16.bf16 "
    "{%0, %1, %2, %3, %4, %5, %6, %7, %8, %9, %10, %11, %12, %13, %14, %15, %16, %17, %18, %19, %20, %21, %22, %23, %24, %25, %26, %27, %28, %29, %30, %31}, {%32,%33,%34,%35}, %36, p, 1, 1, 0;\n}\n"
    : "=f"(d[0]), "=f"(d[1]), "=f"(d[2]), "=f"(d[3]), "=f"(d[4]), "=f"(d[5]), "=f"(d[6]), "=f"(d[7]), "=f"(d[8]), "=f"(d[9]), "=f"(d[10]), "=f"(d[11]), "=f"(d[12]), "=f"(d[13]), "=f"(d[14]), "=f"(d[15]), "=f"(d[16]), "=f"(d[17]), "=f"(d[18]), "=f"(d[19]), "=f"(d[20]), "=f"(d[21]), "=f"(d[22]), "=f"(d[23]), "=f"(d[24]), "=f"(d[25]), "=f"(d[26]), "=f"(d[27]), "=f"(d[28]), "=f"(d[29]), "=f"(d[30]), "=f"(d[31])
    : "r"(a0), "r"(a1), "r"(a2), "r"(a3), "l"(db));
}
__device__ __forceinline__ void wgmma_rs_n24_tb(float (&d)[12], uint32_t a0, uint32_t a1, uint32_t a2, uint32_t a3, uint64_t db, int sd) {
  asm volatile("{\n.reg .pred p;\nsetp.ne.b32 p, %17, 0;\n"
    "wgmma.mma_async.sync.aligned.m64n24k16.f32.bf16.bf16 "
    "{%0, %1, %2, %3, %4, %5, %6, %7, %8, %9, %10, %11}, {%12,%13,%14,%15}, %16, p, 1, 1, 1;\n}\n"
    : "+f"(d[0]), "+f"(d[1]), "+f"(d[2]), "+f"(d[3]), "+f"(d[4]), "+f"(d[5]), "+f"(d[6]), "+f"(d[7]), "+f"(d[8]), "+f"(d[9]), "+f"(d[10]), "+f"(d[11])
    : "r"(a0), "r"(a1), "r"(a2), "r"(a3), "l"(db), "r"(sd));
}

__device__ __forceinline__ float silu_ref(float c) { return bf_round(c / (1.0f + __expf(-c))); }

__global__ void __launch_bounds__(256) k0_mod_ln(const bf16* __restrict__ x, const bf16* __restrict__ c, const bf16* __restrict__ wmod) {
  __shared__ float red[8][32];
  TL(0, 0);
  pdl_launch();
  if (blockIdx.x == 127 && threadIdx.x == 0) g_epoch = g_epoch + 1;
  const int t = threadIdx.x, warp = t >> 5, lane = t & 31, b = blockIdx.x;
  const bool do_mod = b < 72;
  const int strip = b % 36, half = b / 36, cq = t & 3, kr = t >> 2;
  uint4 wv[5]; float cs[5];
  if (do_mod) {
#pragma unroll
    for (int j = 0; j < 5; j++) {
      const int kk = kr + 64 * j, k = half * 288 + kk;
      if (kk < 288) { wv[j] = __ldg(reinterpret_cast<const uint4*>(wmod + (size_t)k * (6 * DM) + strip * 32 + cq * 8)); cs[j] = __bfloat162float(c[k]); }
      else { wv[j] = make_uint4(0, 0, 0, 0); cs[j] = 0.f; }
    }
  }
  const int r0 = b * 16 + warp * 2;
  const uint32_t* xr = reinterpret_cast<const uint32_t*>(x + (size_t)r0 * DM);
  uint32_t xv[2][9];
#pragma unroll
  for (int j = 0; j < 9; j++) { xv[0][j] = __ldg(xr + lane + 32 * j); xv[1][j] = __ldg(xr + 288 + lane + 32 * j); }
  {
    float s0 = 0.f, s1 = 0.f;
#pragma unroll
    for (int j = 0; j < 9; j++) { s0 += bf_lo(xv[0][j]) + bf_hi(xv[0][j]); s1 += bf_lo(xv[1][j]) + bf_hi(xv[1][j]); }
#pragma unroll
    for (int o = 16; o; o >>= 1) { s0 += __shfl_xor_sync(0xffffffffu, s0, o); s1 += __shfl_xor_sync(0xffffffffu, s1, o); }
    const float m0 = s0 * (1.0f / DM), m1 = s1 * (1.0f / DM);
    float v0 = 0.f, v1 = 0.f;
#pragma unroll
    for (int j = 0; j < 9; j++) {
      float d;
      d = bf_lo(xv[0][j]) - m0; v0 = fmaf(d, d, v0); d = bf_hi(xv[0][j]) - m0; v0 = fmaf(d, d, v0);
      d = bf_lo(xv[1][j]) - m1; v1 = fmaf(d, d, v1); d = bf_hi(xv[1][j]) - m1; v1 = fmaf(d, d, v1);
    }
#pragma unroll
    for (int o = 16; o; o >>= 1) { v0 += __shfl_xor_sync(0xffffffffu, v0, o); v1 += __shfl_xor_sync(0xffffffffu, v1, o); }
    const float rs0 = 1.0f / sqrtf(v0 * (1.0f / DM) + 1e-5f), rs1 = 1.0f / sqrtf(v1 * (1.0f / DM) + 1e-5f);
    uint32_t* o32 = reinterpret_cast<uint32_t*>(g_xn + (size_t)r0 * DM);
#pragma unroll
    for (int j = 0; j < 9; j++) {
      o32[lane + 32 * j] = pack_bf16((bf_lo(xv[0][j]) - m0) * rs0, (bf_hi(xv[0][j]) - m0) * rs0);
      o32[288 + lane + 32 * j] = pack_bf16((bf_lo(xv[1][j]) - m1) * rs1, (bf_hi(xv[1][j]) - m1) * rs1);
    }
  }
  TL(0, 2);
  if (do_mod) {
    float acc[8];
#pragma unroll
    for (int i = 0; i < 8; i++) acc[i] = 0.f;
#pragma unroll
    for (int j = 0; j < 5; j++) {
      const float s = silu_ref(cs[j]);
      const uint32_t w[4] = {wv[j].x, wv[j].y, wv[j].z, wv[j].w};
#pragma unroll
      for (int i = 0; i < 4; i++) { acc[2 * i] = fmaf(s, bf_lo(w[i]), acc[2 * i]); acc[2 * i + 1] = fmaf(s, bf_hi(w[i]), acc[2 * i + 1]); }
    }
#pragma unroll
    for (int i = 0; i < 8; i++) {
#pragma unroll
      for (int o = 4; o < 32; o <<= 1) acc[i] += __shfl_xor_sync(0xffffffffu, acc[i], o);
    }
    if (lane < 4) {
#pragma unroll
      for (int i = 0; i < 8; i++) red[warp][lane * 8 + i] = acc[i];
    }
    __syncthreads();
    if (t < 32) {
      float s = 0.f;
#pragma unroll
      for (int w = 0; w < 8; w++) s += red[w][t];
      g_modp[half * 1152 + strip * 32 + t] = s;
    }
  }
  TL(0, 7);
}

__device__ __forceinline__ void mod_tail(const bf16* __restrict__ c, const bf16* __restrict__ wmod, int part, float* smf  ) {
  const int t = threadIdx.x;
  float* sc = smf;
  float* red = smf + 576;
  for (int k = t; k < DM; k += 512) sc[k] = silu_ref(__bfloat162float(c[k]));
  __syncthreads();
  const int cg = t % 72, rg = t / 72;
  float acc[8];
#pragma unroll
  for (int i = 0; i < 8; i++) acc[i] = 0.f;
  if (rg < 7) {
    const bf16* w = wmod + 1152 + part * 576 + cg * 8;
#pragma unroll 1
    for (int k0 = rg; k0 < DM; k0 += 7 * 12) {
      uint4 v[12];
#pragma unroll
      for (int j = 0; j < 12; j++) { const int k = k0 + 7 * j; v[j] = k < DM ? __ldg(reinterpret_cast<const uint4*>(w + (size_t)k * (6 * DM))) : make_uint4(0, 0, 0, 0); }
#pragma unroll
      for (int j = 0; j < 12; j++) {
        const int k = k0 + 7 * j;
        const float s = k < DM ? sc[k] : 0.f;
        acc[0] = fmaf(s, bf_lo(v[j].x), acc[0]); acc[1] = fmaf(s, bf_hi(v[j].x), acc[1]); acc[2] = fmaf(s, bf_lo(v[j].y), acc[2]); acc[3] = fmaf(s, bf_hi(v[j].y), acc[3]);
        acc[4] = fmaf(s, bf_lo(v[j].z), acc[4]); acc[5] = fmaf(s, bf_hi(v[j].z), acc[5]); acc[6] = fmaf(s, bf_lo(v[j].w), acc[6]); acc[7] = fmaf(s, bf_hi(v[j].w), acc[7]);
      }
    }
#pragma unroll
    for (int i = 0; i < 8; i++) red[rg * 576 + cg * 8 + i] = acc[i];
  }
  __syncthreads();
  for (int col = t; col < 576; col += 512) {
    float s = 0.f;
#pragma unroll
    for (int r = 0; r < 7; r++) s += red[r * 576 + col];
    g_mod[1152 + part * 576 + col] = __float2bfloat16_rn(s);
  }
}

constexpr int K1_NST = 5;
constexpr int K1_A = 0, K1_W = 147456, K1_MOD = K1_W + K1_NST * 16384, K1_RED = K1_MOD + 2304, K1_BAR = K1_RED + 256;
constexpr int K1_SMEM = K1_BAR + 8 * (10 + 2 * K1_NST);
#define QSCALE (0.23570226039551584f * 1.4426950408889634f)
#define POLY_MASK 0xFC
__host__ __device__ constexpr bool poly_block(int b) {
  return (POLY_MASK >> b) & 1;
}
constexpr uint32_t KPAD_POLY = 0x42FE47C0u;
constexpr uint32_t VPAD_ONE  = 0x00003F80u;

template <int ST>
__device__ __forceinline__ void k1_load_a(uint32_t (&A)[2][4], const uint32_t (&aoff)[4], uint32_t mtab) {
#pragma unroll
  for (int j = 0; j < 2; j++) {
    ldsm4(A[j], aoff[(ST & 1) * 2 + j] + (ST >> 1) * 16384);
    const uint4 m = lds128(mtab + (ST * 2 + j) * 64);
    A[j][0] = hfma2(A[j][0], m.x, m.z); A[j][1] = hfma2(A[j][1], m.x, m.z);
    A[j][2] = hfma2(A[j][2], m.y, m.w); A[j][3] = hfma2(A[j][3], m.y, m.w);
  }
}
template <int ST>
__device__ __forceinline__ void k1_steps(float (&acc)[108], uint32_t (&A)[3][2][4], const uint32_t (&aoff)[4], uint32_t mtab, uint64_t db0,
                                         uint32_t bx, uint32_t bwf, uint32_t rbe, bool releaser) {
  if constexpr (ST < 18) {
    constexpr int s = ST % K1_NST;
    mbar_wait(bwf + 8 * s, (ST / K1_NST) & 1);
    fence_regs(A[ST % 3][0]); fence_regs(A[ST % 3][1]);
    wg_fence();
#pragma unroll
    for (int j = 0; j < 2; j++)
      wgmma_rs_n216_tb(acc, A[ST % 3][j][0], A[ST % 3][j][1], A[ST % 3][j][2], A[ST % 3][j][3], db0 + (uint64_t)(s * 1024 + j * 128), 1);
    wg_commit();
    if constexpr (ST + 1 < 18) {
      if constexpr (((ST + 1) & 1) == 0) mbar_wait(bx + 8 * ((ST + 1) >> 1), 0);
      k1_load_a<ST + 1>(A[(ST + 1) % 3], aoff, mtab);
    }
    if constexpr (ST > 0) {
      wg_wait<1>();
      if (ST - 1 + K1_NST < 18 && releaser) mbar_arrive_remote(rbe + 8 * ((ST - 1) % K1_NST));
    }
    k1_steps<ST + 1>(acc, A, aoff, mtab, db0, bx, bwf, rbe, releaser);
  }
}

__host__ __device__ constexpr int k1_off(int I, int Q) {
  const int col = 8 * I + 2 * Q, sl = col / 18, d = col % 18;
  return sl * 6144 + (d >> 3) * 128 + (d & 7) * 2 - 4 * Q;
}
template <int I>
__device__ __forceinline__ void k1_stage_block(const float (&acc)[108], uint32_t base, int q4, int nq) {
  uint32_t a = base + k1_off(I, 0);
  if constexpr (k1_off(I, 1) != k1_off(I, 0)) a += q4 >= 1 ? k1_off(I, 1) - k1_off(I, 0) : 0;
  if constexpr (k1_off(I, 2) != k1_off(I, 1)) a += q4 >= 2 ? k1_off(I, 2) - k1_off(I, 1) : 0;
  if constexpr (k1_off(I, 3) != k1_off(I, 2)) a += q4 >= 3 ? k1_off(I, 3) - k1_off(I, 2) : 0;
  constexpr int s0 = (8 * I) / 18, s3 = (8 * I + 6) / 18, qs = s0 == s3 ? 4 : (18 * s3 - 8 * I) / 2;
  const float sc = ((q4 >= qs ? s3 : s0) < nq) ? QSCALE : 1.0f;
  sts32(a, pack_bf16(acc[4 * I] * sc, acc[4 * I + 1] * sc));
  sts32(a + 384, pack_bf16(acc[4 * I + 2] * sc, acc[4 * I + 3] * sc));
}
template <int G>
__device__ __forceinline__ void k1_stage_group(const float (&acc)[108], uint32_t base, uint32_t pbase, uint32_t kpad, int q4, int nt, int rb, int tid,
                                               uint32_t sb) {
  const int nq = 32 - 12 * nt;
  k1_stage_block<9 * G + 0>(acc, base, q4, nq); k1_stage_block<9 * G + 1>(acc, base, q4, nq); k1_stage_block<9 * G + 2>(acc, base, q4, nq);
  k1_stage_block<9 * G + 3>(acc, base, q4, nq); k1_stage_block<9 * G + 4>(acc, base, q4, nq); k1_stage_block<9 * G + 5>(acc, base, q4, nq);
  k1_stage_block<9 * G + 6>(acc, base, q4, nq); k1_stage_block<9 * G + 7>(acc, base, q4, nq); k1_stage_block<9 * G + 8>(acc, base, q4, nq);
#pragma unroll
  for (int i = 0; i < 2; i++) {
    const int slot = nt * 12 + 4 * G + 2 * i + (tid >> 7);
    const uint32_t pad = slot >= 64 ? VPAD_ONE : (slot >= 32 ? kpad : 0u);
    const uint32_t a = pbase + (4 * G + 2 * i) * 6144;
    sts32(a + 4, pad);
    asm volatile("st.shared.v2.b32 [%0], {%1, %1};" :: "r"(a + 8), "r"(0u) : "memory");
  }
  fence_async_smem();
  bar_sync(1, 256);
  if (tid == 0) {
#pragma unroll
    for (int sl = 4 * G; sl < 4 * G + 4; sl++)
      bulk_s2g(g_qkvp + (size_t)(nt * 12 + sl) * SLOT_BYTES + (size_t)rb * 6144, sb + sl * 6144, 6144);
    bulk_commit();
  }
}

__device__ __forceinline__ void transpose_wo(const bf16* __restrict__ wo, int part, uint8_t* smem) {
  uint32_t* t = reinterpret_cast<uint32_t*>(smem);
  const int tid = threadIdx.x;
  const int cg = tid % 18, kp0 = tid / 18;
  const bf16* src = wo + part * 144 + cg * 8;
#pragma unroll 1
  for (int h = 0; h < 2; h++) {
    uint4 v[9][2];
#pragma unroll
    for (int i = 0; i < 9; i++) {
      const int k = 2 * (kp0 + 16 * (9 * h + i));
      v[i][0] = __ldg(reinterpret_cast<const uint4*>(src + (size_t)k * DM));
      v[i][1] = __ldg(reinterpret_cast<const uint4*>(src + (size_t)(k + 1) * DM));
    }
#pragma unroll
    for (int i = 0; i < 9; i++) {
      const int kp = kp0 + 16 * (9 * h + i);
      const uint32_t a[4] = {v[i][0].x, v[i][0].y, v[i][0].z, v[i][0].w}, b[4] = {v[i][1].x, v[i][1].y, v[i][1].z, v[i][1].w};
#pragma unroll
      for (int j = 0; j < 4; j++) {
        t[(cg * 8 + 2 * j) * 289 + kp] = __byte_perm(a[j], b[j], 0x5410);
        t[(cg * 8 + 2 * j + 1) * 289 + kp] = __byte_perm(a[j], b[j], 0x7632);
      }
    }
  }
  bar_sync(1, 288);
  uint32_t* dst = reinterpret_cast<uint32_t*>(g_woT + (size_t)part * 144 * DM);
#pragma unroll 8
  for (int n = 0; n < 144; n++) dst[n * 288 + tid] = t[n * 289 + tid];
}

__global__ void __launch_bounds__(320, 1) k1_qkv(const __grid_constant__ CUtensorMap tm_xn, const __grid_constant__ CUtensorMap tm_w, const bf16* __restrict__ wo) {
  extern __shared__ __align__(1024) uint8_t smem[];
  if (blockIdx.x < 4) {
    pdl_launch();
    if (threadIdx.x >= 288) return;
    transpose_wo(wo, blockIdx.x, smem);
    pdl_wait();
    return;
  }
  const int bid = blockIdx.x - 4;
  const uint32_t sb = s2u(smem);
  const int tid = threadIdx.x, nt = (bid >> 1) & 7, rb = (bid >> 4) * 2 + (bid & 1);
  const uint32_t bx = sb + K1_BAR, bmp = bx + 72, bwf = bmp + 8, bwe = bwf + 8 * K1_NST;
  TL(1, 0);
  if (tid == 256) {
    for (int i = 0; i < 10; i++) mbar_init(bx + 8 * i, 1);
    for (int i = 0; i < K1_NST; i++) { mbar_init(bwf + 8 * i, 1); mbar_init(bwe + 8 * i, 4); }
    fence_barrier_init();
    tmap_prefetch(&tm_xn); tmap_prefetch(&tm_w);
  }
  __syncthreads();
  cluster_arrive_relaxed();
  pdl_launch();
  if (tid >= 288) {
    if (tid == 288) {
      auto load_x = [&](int c) { mbar_expect(bx + 8 * c, 16384); tma2d(sb + K1_A + c * 16384, &tm_xn, c * 64, rb * 128, bx + 8 * c); };
      pdl_wait();
      mbar_expect(bmp, 4 * DM * 4); bulk_g2s(sb + K1_A + 8 * 16384, g_modp, 4 * DM * 4, bmp);
      load_x(0); load_x(1); load_x(2);
      for (int c = 3; c < 9; c++) { mbar_wait(bx + 8 * (c - 3), 0); if (c == 8) mbar_wait(bwe, 0); load_x(c); }
    }
    __syncwarp();
    cluster_wait();
    return;
  }
  if (tid >= 256) {
    cluster_wait();
    if (tid == 256) {
      const int rank = cluster_rank();
      auto load_w = [&](int st) {
        const int s = st % K1_NST;
        mbar_expect(bwf + 8 * s, 16384);
        for (int g = 2 * rank; g < 2 * rank + 2; g++) tma2d_mc(sb + K1_W + s * 16384 + g * 4096, &tm_w, nt * 216 + g * 64, st * 32, bwf + 8 * s);
      };
      for (int st = 0; st < K1_NST; st++) load_w(st);
      if (rb < 8) for (int b = rb; b < (18 - K1_NST) * 4; b += 8) tma2d_prefetch(&tm_w, nt * 216 + (b & 3) * 64, (K1_NST + (b >> 2)) * 32);
      for (int st = K1_NST; st < 18; st++) {
        mbar_wait(bwe + 8 * (st % K1_NST), (st / K1_NST - 1) & 1);
        load_w(st);
      }
    }
    __syncwarp();
    cluster_arrive_relaxed(); cluster_wait();
    return;
  }
  cluster_wait();
  const int wg = __reduce_max_sync(0xffffffffu, (unsigned)tid >> 7), wtid = tid & 127, warp = (tid >> 5) & 3, lane = tid & 31, g = lane >> 2, q4 = lane & 3;
  const uint32_t rbe = map_cta(bwe, wtid & 1);
  TL(1, 1);
  {
    const float2* mp = reinterpret_cast<const float2*>(smem + K1_A + 8 * 16384);
    mbar_wait(bmp, 0);
    for (int i = tid; i < 288; i += 256) {
      const float2 s0 = mp[i], s1 = mp[576 + i], c0 = mp[288 + i], c1 = mp[576 + 288 + i];
      const uint32_t a = sb + K1_MOD + (i >> 3) * 64 + (i & 3) * 16 + ((i >> 2) & 1) * 4;
      sts32(a, hadd2(pack_bf16(c0.x + c1.x, c0.y + c1.y), 0x3F803F80u));
      sts32(a + 8, pack_bf16(s0.x + s1.x, s0.y + s1.y));
    }
  }
  bar_sync(1, 256);
  TL(1, 4);
  uint32_t aoff[4];
  {
    const int r = wg * 64 + warp * 16 + (lane & 7) + ((lane >> 3) & 1) * 8;
#pragma unroll
    for (int j = 0; j < 4; j++) aoff[j] = opaque(sb + K1_A + r * 128 + (((2 * j + (lane >> 4)) ^ (lane & 7)) << 4));
  }
  const uint32_t mtab = opaque(sb + K1_MOD + q4 * 16);
  float acc[108];
#pragma unroll
  for (int i = 0; i < 108; i++) acc[i] = 0.f;
  const uint64_t db0 = mkdesc(sb + K1_W, 4096, 1024, 1);
  uint32_t A[3][2][4];
  mbar_wait(bx, 0);
  TL(1, 5);
  k1_load_a<0>(A[0], aoff, mtab);
  k1_steps<0>(acc, A, aoff, mtab, db0, bx, bwf, rbe, wtid < 2);
  wg_wait<0>();
  fence_regs(acc);
  cluster_arrive_relaxed();
  TL(1, 2);
  bar_sync(1, 256);
  {
    const int tok = wg * 64 + warp * 16 + g;
    const uint32_t base = opaque(sb + (tok >> 3) * 384 + (tok & 7) * 16 + q4 * 4);
    const int tk = tid & 127;
    const uint32_t pbase = opaque(sb + (tid >> 7) * 6144 + (tk >> 3) * 384 + (tk & 7) * 16 + 256);
    const uint32_t kpad = poly_block((tk >> 3) & 7) ? KPAD_POLY : 0u;
    k1_stage_group<0>(acc, base, pbase, kpad, q4, nt, rb, tid, sb);
    k1_stage_group<1>(acc, base, pbase, kpad, q4, nt, rb, tid, sb);
    k1_stage_group<2>(acc, base, pbase, kpad, q4, nt, rb, tid, sb);
  }
  TL(1, 3);
  if (nt * 12 < 64) {
    const int tok = tid & 127;
    float* red = reinterpret_cast<float*>(smem + K1_RED);
#pragma unroll
    for (int i = 0; i < 6; i++) {
      const int sl = (tid >> 7) + 2 * i;
      const uint32_t a = sb + sl * 6144 + (tok >> 3) * 384 + (tok & 7) * 16;
      const uint4 v0 = lds128(a), v1 = lds128(a + 128);
      const uint32_t v2 = lds32(a + 256);
      float n2 = 0.f;
      const uint32_t w[9] = {v0.x, v0.y, v0.z, v0.w, v1.x, v1.y, v1.z, v1.w, v2};
#pragma unroll
      for (int j = 0; j < 9; j++) { n2 = fmaf(bf_lo(w[j]), bf_lo(w[j]), n2); n2 = fmaf(bf_hi(w[j]), bf_hi(w[j]), n2); }
      const uint32_t mx = __reduce_max_sync(0xffffffffu, __float_as_uint(n2) & 0x7FFFFFFFu);
      if (lane == 0) red[sl * 4 + warp] = __uint_as_float(mx);
    }
    bar_sync(1, 256);
    if (tid >= 32 && tid < 44) {
      const int sl = tid - 32, slot = nt * 12 + sl;
      const uint32_t* r = reinterpret_cast<const uint32_t*>(red) + sl * 4;
      if (slot < 64) g_nrm[slot * 16 + rb] = __uint_as_float(max(max(r[0], r[1]), max(r[2], r[3])));
    }
  }
  if (tid == 0) bulk_wait_read();
  TL(1, 7);
  cluster_wait();
}

constexpr int K2_K = 0, K2_V = SLOT_BYTES, K2_Q = 2 * SLOT_BYTES, K2_BAR = K2_Q + 512 * 48, K2_SMEM = K2_BAR + 8 * 19;
constexpr uint32_t EXP_C2 = 0x3EA93EA9u, EXP_C1 = 0x3B4E3B4Eu, EXP_C0 = 0x3F2C3F2Cu;
constexpr int K2_TD = 8 * 384 / 16;

__device__ __forceinline__ void attn_qk(float (&S)[32], const uint32_t (&q)[8], uint64_t kd) {
  wgmma_rs0_n64(S, q[0], q[1], q[2], q[3], kd);
  wgmma_rs_n64(S, q[4], q[5], q[6], q[7], kd + 16, 1);
}
__device__ __forceinline__ void attn_pv(float (&O)[12], const uint32_t (&P)[16], uint64_t vd) {
#pragma unroll
  for (int kk = 0; kk < 4; kk++) wgmma_rs_n24_tb(O, P[4 * kk], P[4 * kk + 1], P[4 * kk + 2], P[4 * kk + 3], vd + kk * 48, 1);
}
__device__ __forceinline__ void attn_exp(float (&S)[32], uint32_t c2, uint32_t cone) {
#pragma unroll
  for (int b = 0; b < 8; b++) {
    if (poly_block(b)) {
#pragma unroll
      for (int h = 0; h < 2; h++) {
        uint32_t w, y;
        asm("prmt.b32 %0, %1, %2, 0x5410;" : "=r"(w) : "r"(__float_as_uint(S[4 * b + 2 * h])), "r"(__float_as_uint(S[4 * b + 2 * h + 1])));
        asm("lop3.b32 %0, %1, 0x007F007F, %2, 0xEA;" : "=r"(y) : "r"(w), "r"(cone));
        const uint32_t p = hfma2(hfma2(y, c2, EXP_C1), y, EXP_C0);
        S[4 * b + 2 * h] = __uint_as_float(w);
        S[4 * b + 2 * h + 1] = __uint_as_float(p);
      }
    } else {
#pragma unroll
      for (int j = 0; j < 4; j++) S[4 * b + j] = ex2(S[4 * b + j]);
    }
  }
}
__device__ __forceinline__ void attn_pack(const float (&S)[32], uint32_t (&P)[16]) {
#pragma unroll
  for (int i = 0; i < 16; i++) {
    if (poly_block(i >> 1)) asm("lop3.b32 %0, %1, %2, 0xFF80FF80, 0xE4;" : "=r"(P[i]) : "r"(__float_as_uint(S[2 * i])), "r"(__float_as_uint(S[2 * i + 1])));
    else P[i] = pack_bf16(S[2 * i], S[2 * i + 1]);
  }
}

template <bool WAIT>
__device__ __forceinline__ void attn_fast_pass(float (&O)[12], const uint32_t (&q)[8], uint64_t kd, uint64_t vd, uint32_t bar) {
  float S[32]; uint32_t P[16];
  const uint32_t c2 = opaque(EXP_C2), cone = opaque(0x3F803F80u);
  if (WAIT) mbar_wait(bar, 0);
  wg_fence();
  attn_qk(S, q, kd);
  wg_commit();
  wg_wait<0>();
  fence_regs(S);
  attn_exp(S, c2, cone);
  attn_pack(S, P);
  auto step = [&]() {
    kd += K2_TD;
    fence_regs(P); fence_regs(O);
    wg_fence();
    attn_qk(S, q, kd);
    wg_commit();
    attn_pv(O, P, vd);
    wg_commit();
    vd += K2_TD;
    wg_wait<1>();
    fence_regs(S);
    attn_exp(S, c2, cone);
    fence_regs(S);
    wg_wait<0>();
    fence_regs(S); fence_regs(O);
    attn_pack(S, P);
  };
#pragma unroll 1
  for (int c = 1; c < 16; c++) {
    step();
    if (WAIT) mbar_wait(bar + 8 * c, 0);
    step();
  }
  step();
  fence_regs(P); fence_regs(O);
  wg_fence();
  attn_pv(O, P, vd);
  wg_commit();
  wg_wait<0>();
  fence_regs(O);
}

__device__ __forceinline__ void attn_safe_pass(float (&O)[12], const uint32_t (&q)[8], uint64_t kd, uint64_t vd, uint32_t bar) {
  float S[32]; uint32_t P[16];
  float m0 = -INFINITY, m1 = -INFINITY;
#pragma unroll 1
  for (int j = 0; j < 32; j++) {
    if ((j & 1) == 0) mbar_wait(bar + 8 * (j >> 1), 0);
    wg_fence();
    attn_qk(S, q, kd);
    wg_commit();
    wg_wait<0>();
    fence_regs(S);
    float x0 = m0, x1 = m1;
#pragma unroll
    for (int b = 0; b < 8; b++) { x0 = fmaxf(x0, fmaxf(S[4 * b], S[4 * b + 1])); x1 = fmaxf(x1, fmaxf(S[4 * b + 2], S[4 * b + 3])); }
    x0 = fmaxf(x0, __shfl_xor_sync(0xffffffffu, x0, 1)); x0 = fmaxf(x0, __shfl_xor_sync(0xffffffffu, x0, 2));
    x1 = fmaxf(x1, __shfl_xor_sync(0xffffffffu, x1, 1)); x1 = fmaxf(x1, __shfl_xor_sync(0xffffffffu, x1, 2));
    const float a0 = ex2(m0 - x0), a1 = ex2(m1 - x1);
    m0 = x0; m1 = x1;
#pragma unroll
    for (int b = 0; b < 3; b++) { O[4 * b] *= a0; O[4 * b + 1] *= a0; O[4 * b + 2] *= a1; O[4 * b + 3] *= a1; }
#pragma unroll
    for (int b = 0; b < 8; b++) {
      P[2 * b] = pack_bf16(ex2(S[4 * b] - m0), ex2(S[4 * b + 1] - m0));
      P[2 * b + 1] = pack_bf16(ex2(S[4 * b + 2] - m1), ex2(S[4 * b + 3] - m1));
    }
    fence_regs(P); fence_regs(O);
    wg_fence();
    attn_pv(O, P, vd);
    wg_commit();
    wg_wait<0>();
    fence_regs(O);
    kd += K2_TD; vd += K2_TD;
  }
}

__global__ void __launch_bounds__(512, 1) k2_attn(const bf16* __restrict__ cvec, const bf16* __restrict__ wmod,
                                                   const bf16* __restrict__ w1, const bf16* __restrict__ w2) {
  extern __shared__ __align__(1024) uint8_t smem[];
  const uint32_t sb = s2u(smem);
  const int head = blockIdx.x >> 2, qg = blockIdx.x & 3;
  const int tid = threadIdx.x, wg = __reduce_max_sync(0xffffffffu, (unsigned)tid >> 7), warp = (tid >> 5) & 3, lane = tid & 31, g = lane >> 2, q4 = lane & 3;
  const uint32_t bar = sb + K2_BAR;
  TL(2, 0);
  if (tid == 0) {
    for (int i = 0; i < 18; i++) mbar_init(bar + 8 * i, 1);
    fence_barrier_init();
  }
  __syncthreads();
  if (blockIdx.x >= 128) {
    mod_tail(cvec, wmod, blockIdx.x - 128, reinterpret_cast<float*>(smem));
    pdl_wait();
    return;
  }
  pdl_wait();
  pdl_launch();
  TL(2, 3);
  if ((tid >> 5) == 1) {
    uint32_t nv = 0;
    if (lane < 16) nv = __float_as_uint(__ldcg(&g_nrm[(32 + head) * 16 + lane]));
    else if (lane < 20) nv = __float_as_uint(__ldcg(&g_nrm[head * 16 + qg * 4 + lane - 16]));
    const uint32_t km = __reduce_max_sync(0xffffffffu, lane < 16 ? nv : 0u), qm = __reduce_max_sync(0xffffffffu, lane < 16 ? 0u : nv);
    if (lane == 0) sts32(bar + 8 * 18, __uint_as_float(km) * __uint_as_float(qm) <= 4096.0f ? 1u : 0u);
  }
  {
    const uint8_t* Qg = g_qkvp + (size_t)head * SLOT_BYTES + (size_t)qg * 512 * 48;
    const uint8_t* Kg = g_qkvp + (size_t)(32 + head) * SLOT_BYTES;
    const uint8_t* Vg = g_qkvp + (size_t)(64 + head) * SLOT_BYTES;
    auto load_chunk = [&](int c) {
      mbar_expect(bar + 8 * c, 2 * 6144);
      bulk_g2s(sb + K2_K + c * 6144, Kg + c * 6144, 6144, bar + 8 * c);
      bulk_g2s(sb + K2_V + c * 6144, Vg + c * 6144, 6144, bar + 8 * c);
    };
    if (tid == 0) {
      mbar_expect(bar + 8 * 16, 4 * 3072);
      for (int w = 0; w < 4; w++) bulk_g2s(sb + K2_Q + w * 6144, Qg + w * 6144, 3072, bar + 8 * 16);
      load_chunk(0); load_chunk(1);
    }
    __syncthreads();
    if (tid == 32) {
      for (int c = 2; c < 16; c++) load_chunk(c);
      mbar_expect(bar + 8 * 17, 4 * 3072);
      for (int w = 0; w < 4; w++) bulk_g2s(sb + K2_Q + w * 6144 + 3072, Qg + w * 6144 + 3072, 3072, bar + 8 * 17);
    }
    __syncwarp();
  }
  TL(2, 1);
  const bool fast = lds32(bar + 8 * 18) != 0;
  const uint64_t kd = mkdesc(sb + K2_K, 128, 384, 0);
  const uint64_t vd = mkdesc(sb + K2_V, 384, 128, 0);
#pragma unroll 1
  for (int it = 0; it < 2; it++) {
    const int qt = wg * 2 + it;
    mbar_wait(bar + 8 * (16 + it), 0);
    if (it == 0) TL(2, 4);
    uint32_t q[8];
    {
      const uint32_t base = sb + K2_Q + (qt * 8 + warp * 2) * 384 + g * 16 + q4 * 4;
#pragma unroll
      for (int j = 0; j < 3; j++) { q[2 * j] = lds32(base + j * 128); q[2 * j + 1] = lds32(base + 384 + j * 128); }
      if (fast && q4 == 1) { q[4] = 0x3F803F80u; q[5] = 0x3F803F80u; }
      q[6] = opaque(0u); q[7] = opaque(0u);
    }
    if (it == 1 && tid == 0) {
      const char* a = reinterpret_cast<const char*>(w1) + (size_t)blockIdx.x * (DM * FF * 2 / 128);
      const char* b = reinterpret_cast<const char*>(w2) + (size_t)blockIdx.x * (DM * FF * 2 / 128);
      asm volatile("cp.async.bulk.prefetch.L2.global [%0], %1;" :: "l"(a), "r"(DM * FF * 2 / 128) : "memory");
      asm volatile("cp.async.bulk.prefetch.L2.global [%0], %1;" :: "l"(b), "r"(DM * FF * 2 / 128) : "memory");
    }
    float O[12];
#pragma unroll
    for (int i = 0; i < 12; i++) O[i] = 0.f;
    if (fast) {
      if (it == 0) attn_fast_pass<true>(O, q, kd, vd, bar);
      else attn_fast_pass<false>(O, q, kd, vd, bar);
    } else {
      attn_safe_pass(O, q, kd, vd, bar);
    }
    const float l0 = __shfl_sync(0xffffffffu, O[8], (lane & ~3) | 1), l1 = __shfl_sync(0xffffffffu, O[10], (lane & ~3) | 1);
    const float r0 = __frcp_rn(l0), r1 = __frcp_rn(l1);
    const int row = qg * 512 + qt * 64 + warp * 16 + g;
    uint32_t* o0 = reinterpret_cast<uint32_t*>(g_o + (size_t)row * DM + head * DHEAD + q4 * 2);
    uint32_t* o1 = o0 + 8 * DM / 2;
    o0[0] = pack_bf16(O[0] * r0, O[1] * r0);  o1[0] = pack_bf16(O[2] * r1, O[3] * r1);
    o0[4] = pack_bf16(O[4] * r0, O[5] * r0);  o1[4] = pack_bf16(O[6] * r1, O[7] * r1);
    if (q4 == 0) { o0[8] = pack_bf16(O[8] * r0, O[9] * r0);  o1[8] = pack_bf16(O[10] * r1, O[11] * r1); }
  }
  TL(2, 7);
}

#define K3_SLEEP 200
constexpr int K3_A = 0, K3_W = 147456, K3_X = K3_W, K3_MOD = K3_W + 9 * 9216, K3_BAR = K3_MOD + 3 * 144 + 16;
constexpr int K3_SMEM = K3_BAR + 8 * (9 + 9 + 3);

__global__ void __launch_bounds__(288, 1) k3_wo(const __grid_constant__ CUtensorMap tm_o, const __grid_constant__ CUtensorMap tm_wo,
                                                const __grid_constant__ CUtensorMap tm_x, const __grid_constant__ CUtensorMap tm_x2,
                                                const __grid_constant__ CUtensorMap tm_h2) {
  extern __shared__ __align__(1024) uint8_t smem[];
  const uint32_t sb = s2u(smem);
  const int tid = threadIdx.x, nt = blockIdx.x & 7, rb = blockIdx.x >> 3;
  const uint32_t bw = sb + K3_BAR, baf = bw + 72, bxb = baf + 72, bmd = bxb + 8, bxe = bmd + 8;
  TL(3, 0);
  if (tid == 256) {
    for (int i = 0; i < 20; i++) mbar_init(bw + 8 * i, 1);
    mbar_init(bxe, 2);
    fence_barrier_init();
    tmap_prefetch(&tm_o); tmap_prefetch(&tm_wo); tmap_prefetch(&tm_x); tmap_prefetch(&tm_x2); tmap_prefetch(&tm_h2);
  }
  __syncthreads();
  cluster_arrive_relaxed();
  pdl_launch();
  if (tid >= 256) {
    if (tid == 256)
      for (int c = 0; c < 9; c++) { mbar_expect(bw + 8 * c, 9216); tma2d(sb + K3_W + c * 9216, &tm_wo, c * 64, nt * 72, bw + 8 * c); }
    __syncwarp();
    cluster_wait();
    if (tid == 256) {
      const int rank = cluster_rank();
      pdl_wait();
      for (int c = 0; c < 9; c++) {
        mbar_expect(baf + 8 * c, 16384);
        tma2d_mc(sb + K3_A + c * 16384 + rank * 8192, &tm_o, c * 64, rb * 128 + rank * 64, baf + 8 * c);
      }
      mbar_expect(bmd, 3 * 144);
      for (int v = 0; v < 3; v++) bulk_g2s(sb + K3_MOD + v * 144, g_mod + (2 + v) * DM + nt * 72, 144, bmd);
      mbar_wait(bxe, 0);
      mbar_expect(bxb, 18432); tma2d(sb + K3_X, &tm_x, nt * 72, rb * 128, bxb);
      cluster_arrive_relaxed(); cluster_wait();
    }
    return;
  }
  const int wg = __reduce_max_sync(0xffffffffu, (unsigned)tid >> 7), wtid = tid & 127, warp = (tid >> 5) & 3, lane = tid & 31, g = lane >> 2, q4 = lane & 3;
  const int lrow = wg * 64 + warp * 16 + g;
  cluster_wait();
  pdl_wait();
  TL(3, 1);
  const uint32_t tag = __ldcg(&g_epoch);
  float acc[36];
#pragma unroll
  for (int i = 0; i < 36; i++) acc[i] = 0.f;
  const uint64_t da0 = mkdesc(sb + K3_A + wg * 8192, 16, 1024, 1);
  const uint64_t db0 = mkdesc(sb + K3_W, 16, 1024, 1);
#pragma unroll 1
  for (int c = 0; c < 9; c++) {
    mbar_wait(bw + 8 * c, 0);
    mbar_wait(baf + 8 * c, 0);
    wg_fence();
#pragma unroll
    for (int j = 0; j < 4; j++) wgmma_ss_n72(acc, da0 + (uint64_t)(c * 1024 + j * 2), db0 + (uint64_t)(c * 576 + j * 2), 1);
    wg_commit();
    if (c == 2) { wg_wait<1>(); if (wtid == 0) mbar_arrive(bxe); }
  }
  wg_wait<0>();
  fence_regs(acc);
  cluster_arrive_relaxed();
  TL(3, 2);
  mbar_wait(bmd, 0);
  mbar_wait(bxb, 0);
  const uint32_t xa = sb + K3_X + lrow * 144 + q4 * 4, ma = sb + K3_MOD + q4 * 4;
  float s0 = 0.f, s1 = 0.f;
#pragma unroll
  for (int i = 0; i < 9; i++) {
    const uint32_t x0 = lds32(xa + 16 * i), x1 = lds32(xa + 8 * 144 + 16 * i), ga = lds32(ma + 16 * i);
    const float g0 = bf_lo(ga), g1 = bf_hi(ga);
    const uint32_t p0 = pack_bf16(fmaf(g0, acc[4 * i], bf_lo(x0)), fmaf(g1, acc[4 * i + 1], bf_hi(x0)));
    const uint32_t p1 = pack_bf16(fmaf(g0, acc[4 * i + 2], bf_lo(x1)), fmaf(g1, acc[4 * i + 3], bf_hi(x1)));
    sts32(xa + 16 * i, p0); sts32(xa + 8 * 144 + 16 * i, p1);
    acc[4 * i] = bf_lo(p0); acc[4 * i + 1] = bf_hi(p0); acc[4 * i + 2] = bf_lo(p1); acc[4 * i + 3] = bf_hi(p1);
    s0 += acc[4 * i] + acc[4 * i + 1]; s1 += acc[4 * i + 2] + acc[4 * i + 3];
  }
  s0 += __shfl_xor_sync(0xffffffffu, s0, 1); s1 += __shfl_xor_sync(0xffffffffu, s1, 1);
  s0 += __shfl_xor_sync(0xffffffffu, s0, 2); s1 += __shfl_xor_sync(0xffffffffu, s1, 2);
  const float m0 = s0 * (1.0f / 72), m1 = s1 * (1.0f / 72);
  float v0 = 0.f, v1 = 0.f;
#pragma unroll
  for (int i = 0; i < 9; i++) {
    float d;
    d = acc[4 * i] - m0; v0 = fmaf(d, d, v0); d = acc[4 * i + 1] - m0; v0 = fmaf(d, d, v0);
    d = acc[4 * i + 2] - m1; v1 = fmaf(d, d, v1); d = acc[4 * i + 3] - m1; v1 = fmaf(d, d, v1);
  }
  v0 += __shfl_xor_sync(0xffffffffu, v0, 1); v1 += __shfl_xor_sync(0xffffffffu, v1, 1);
  v0 += __shfl_xor_sync(0xffffffffu, v0, 2); v1 += __shfl_xor_sync(0xffffffffu, v1, 2);
  if (q4 < 2) {
    const float mm = q4 ? m1 : m0, vv = q4 ? v1 : v0;
    asm volatile("st.relaxed.gpu.global.v2.b64 [%0], {%1, %2};"
                 :: "l"(&g_stats[(rb * 8 + nt) * 128 + lrow + 8 * q4]), "l"(((uint64_t)tag << 32) | __float_as_uint(mm)), "l"(((uint64_t)tag << 32) | __float_as_uint(vv)) : "memory");
  }
  fence_async_smem();
  bar_sync(1, 256);
  TL(3, 3);
  if (tid == 0) { tma2d_store(&tm_x2, sb + K3_X, nt * 72, rb * 128); bulk_commit(); }
  float mean0, mean1, rs0, rs1;
  {
    uint64_t w[8];
    const uint4* pa = &g_stats[(rb * 8 + 2 * q4) * 128 + lrow];
    for (int it = 0; it < (1 << 20); it++) {
      asm volatile("ld.relaxed.gpu.global.v2.b64 {%0, %1}, [%2];" : "=l"(w[0]), "=l"(w[1]) : "l"(pa) : "memory");
      asm volatile("ld.relaxed.gpu.global.v2.b64 {%0, %1}, [%2];" : "=l"(w[2]), "=l"(w[3]) : "l"(pa + 128) : "memory");
      asm volatile("ld.relaxed.gpu.global.v2.b64 {%0, %1}, [%2];" : "=l"(w[4]), "=l"(w[5]) : "l"(pa + 8) : "memory");
      asm volatile("ld.relaxed.gpu.global.v2.b64 {%0, %1}, [%2];" : "=l"(w[6]), "=l"(w[7]) : "l"(pa + 136) : "memory");
      bool ok = true;
#pragma unroll
      for (int j = 0; j < 8; j++) ok = ok && (uint32_t)(w[j] >> 32) == tag;
      if (__all_sync(0xffffffffu, ok)) break;
      __nanosleep(K3_SLEEP);
    }
    const float ax = __uint_as_float((uint32_t)w[0]), ay = __uint_as_float((uint32_t)w[1]), az = __uint_as_float((uint32_t)w[2]), aw = __uint_as_float((uint32_t)w[3]);
    const float bx = __uint_as_float((uint32_t)w[4]), by = __uint_as_float((uint32_t)w[5]), bz = __uint_as_float((uint32_t)w[6]), bw_ = __uint_as_float((uint32_t)w[7]);
    float sa = ax + az, sb_ = bx + bz;
    sa += __shfl_xor_sync(0xffffffffu, sa, 1); sb_ += __shfl_xor_sync(0xffffffffu, sb_, 1);
    sa += __shfl_xor_sync(0xffffffffu, sa, 2); sb_ += __shfl_xor_sync(0xffffffffu, sb_, 2);
    mean0 = sa * 0.125f; mean1 = sb_ * 0.125f;
    float ma2 = ay + aw + 72.f * ((ax - mean0) * (ax - mean0) + (az - mean0) * (az - mean0));
    float mb2 = by + bw_ + 72.f * ((bx - mean1) * (bx - mean1) + (bz - mean1) * (bz - mean1));
    ma2 += __shfl_xor_sync(0xffffffffu, ma2, 1); mb2 += __shfl_xor_sync(0xffffffffu, mb2, 1);
    ma2 += __shfl_xor_sync(0xffffffffu, ma2, 2); mb2 += __shfl_xor_sync(0xffffffffu, mb2, 2);
    rs0 = rsqrtf(ma2 * (1.0f / DM) + 1e-5f); rs1 = rsqrtf(mb2 * (1.0f / DM) + 1e-5f);
  }
  TL(3, 4);
  {
    const uint32_t ha = sb + K3_A + lrow * 144 + q4 * 4;
#pragma unroll
    for (int i = 0; i < 9; i++) {
      const uint32_t c1p = hadd2(lds32(ma + 288 + 16 * i), 0x3F803F80u), sh = lds32(ma + 144 + 16 * i);
      sts32(ha + 16 * i, hfma2(hfma2(pack_bf16((acc[4 * i] - mean0) * rs0, (acc[4 * i + 1] - mean0) * rs0), c1p, sh), 0x3F003F00u, 0x80008000u));
      sts32(ha + 8 * 144 + 16 * i, hfma2(hfma2(pack_bf16((acc[4 * i + 2] - mean1) * rs1, (acc[4 * i + 3] - mean1) * rs1), c1p, sh), 0x3F003F00u, 0x80008000u));
    }
  }
  fence_async_smem();
  bar_sync(1, 256);
  if (tid == 0) { tma2d_store(&tm_h2, sb + K3_A, nt * 72, rb * 128); bulk_commit(); bulk_wait_read(); }
  TL(3, 7);
  cluster_wait();
}

#define K4_BK 64
#define K4_STAGGER 0
constexpr int K4_KS = K4_BK / 16;
constexpr int K4_SPT = 576 / K4_BK;
constexpr int K4_NST = 3 * 64 / K4_BK;
constexpr int K4_STB = K4_BK * 384;
constexpr int K4_A = 0, K4_B = 147456, K4_ST = K4_B + K4_NST * K4_STB, K4_BAR = K4_ST + 8192, K4_SMEM = K4_BAR + 8 * (9 + 2 * K4_NST) + 8;

__device__ __forceinline__ uint32_t silu2(uint32_t v, uint32_t m16, uint32_t mhi) {
  const float lo = __uint_as_float(v * m16), hi = __uint_as_float(v & mhi);
  return pack_bf16(fmaf(lo, tanh_fast(lo), lo), fmaf(hi, tanh_fast(hi), hi));
}
template <int P>
__device__ __forceinline__ void k4_epi(const uint32_t (&pk)[48], uint32_t go, bf16* hp) {
  const uint32_t m16 = go << 16, mhi = 0u - m16;
  constexpr int B = 8 * (P >> 1) + (P & 1);
  uint4 r;
  r.x = silu2(pk[B], m16, mhi); r.y = silu2(pk[B + 2], m16, mhi); r.z = silu2(pk[B + 4], m16, mhi); r.w = silu2(pk[B + 6], m16, mhi);
  asm volatile("st.global.v4.b32 [%0], {%1,%2,%3,%4};" :: "l"(hp + (P & 1) * 8 * FF + 32 * (P >> 1)), "r"(r.x), "r"(r.y), "r"(r.z), "r"(r.w) : "memory");
}
template <int P0, int N>
__device__ __forceinline__ void k4_epi_n(const uint32_t (&pk)[48], uint32_t go, bf16* hp) {
  if constexpr (N > 0) { k4_epi<P0>(pk, go, hp); k4_epi_n<P0 + 1, N - 1>(pk, go, hp); }
}
__host__ __device__ constexpr int k4_first(int i) { return K4_SPT == 9 ? (i * 12 + 8) / 9 : (i * 12 + 17) / 18; }

template <int T, int I>
__device__ __forceinline__ void k4_steps(float (&acc)[96], const uint32_t (&pk)[48], uint64_t da0, uint64_t db0, uint32_t ba, uint32_t bbf,
                                         uint32_t rbe, int wtid, bf16* hp) {
  if constexpr (I < K4_SPT) {
    constexpr int st = T * K4_SPT + I, s = st % K4_NST, k0 = I * K4_KS;
    if (T == 0 && (k0 & 3) == 0) mbar_wait(ba + 8 * (k0 >> 2), 0);
    mbar_wait(bbf + 8 * s, (st / K4_NST) & 1);
    wg_fence();
#pragma unroll
    for (int j = 0; j < K4_KS; j++)
      wgmma_ss_n192_tb(acc, da0 + (uint64_t)(((k0 + j) >> 2) * 1024 + ((k0 + j) & 3) * 2), db0 + (uint64_t)(s * (K4_STB / 16) + j * 128), (I | j) != 0);
    wg_commit();
    if (I > 0) {
      wg_wait<1>();
      if (st - 1 + K4_NST < 3 * K4_SPT && wtid < 2) mbar_arrive_remote(rbe + 8 * ((st - 1) % K4_NST));
    }
    if constexpr (T > 0 && k4_first(I + 1) > k4_first(I)) {
      const uint32_t go = mbar_try(ba, 0);
      k4_epi_n<k4_first(I), k4_first(I + 1) - k4_first(I)>(pk, go, hp);
    }
    k4_steps<T, I + 1>(acc, pk, da0, db0, ba, bbf, rbe, wtid, hp);
  }
}
template <int T>
__device__ __forceinline__ void k4_tile(float (&acc)[96], const uint32_t (&pk)[48], uint64_t da0, uint64_t db0, uint32_t ba, uint32_t bbf,
                                        uint32_t rbe, int wtid, bf16* hprev) {
  k4_steps<T, 0>(acc, pk, da0, db0, ba, bbf, rbe, wtid, hprev);
  wg_wait<0>();
  fence_regs(acc);
  if (T * K4_SPT + K4_SPT - 1 + K4_NST < 3 * K4_SPT && wtid < 2) mbar_arrive_remote(rbe + 8 * ((T * K4_SPT + K4_SPT - 1) % K4_NST));
}
__device__ __forceinline__ void k4_pack(const float (&acc)[96], uint32_t (&pk)[48]) {
#pragma unroll
  for (int i = 0; i < 48; i++) pk[i] = pack_bf16(acc[2 * i], acc[2 * i + 1]);
}

__global__ void __launch_bounds__(384, 1) k4_mlp1(const __grid_constant__ CUtensorMap tm_h2, const __grid_constant__ CUtensorMap tm_w1) {
  extern __shared__ __align__(1024) uint8_t smem[];
  const uint32_t sb = s2u(smem);
  const int tid = threadIdx.x, rb = blockIdx.x & 15, fs = blockIdx.x >> 4;
  const uint32_t ba = sb + K4_BAR, bbf = ba + 72, bbe = bbf + 8 * K4_NST;
  TL(4, 0);
  if (tid == 0) {
    for (int i = 0; i < 9; i++) mbar_init(ba + 8 * i, 1);
    for (int i = 0; i < K4_NST; i++) { mbar_init(bbf + 8 * i, 1); mbar_init(bbe + 8 * i, 4); }
    fence_barrier_init();
    tmap_prefetch(&tm_h2); tmap_prefetch(&tm_w1);
  }
  __syncthreads();
  cluster_arrive_relaxed();
  pdl_launch();
  if (tid < 128) {
    reg_dec<40>();
    if (tid >= 32 && tid < 64) {
      if (tid == 32) {
        pdl_wait();
        for (int c = 0; c < 9; c++) {
          if (c >= 4) mbar_wait(ba + 8 * (c - 4), 0);
          mbar_expect(ba + 8 * c, 16384); tma2d(sb + K4_A + c * 16384, &tm_h2, c * 64, rb * 128, ba + 8 * c);
        }
      }
      __syncwarp();
      cluster_wait();
    } else {
      cluster_wait();
      if (tid == 0) {
        const int rank = cluster_rank();
        for (int st = 0; st < 3 * K4_SPT; st++) {
          const int s = st % K4_NST, t = st / K4_SPT, i = st % K4_SPT;
          if (st >= K4_NST) mbar_wait(bbe + 8 * s, (st / K4_NST - 1) & 1);
          mbar_expect(bbf + 8 * s, K4_STB);
          for (int g = 0; g < 3; g++)
            tma2d_mc(sb + K4_B + s * K4_STB + g * (K4_STB / 3) + rank * (K4_STB / 6), &tm_w1, fs * 576 + t * 192 + g * 64, i * K4_BK + rank * (K4_BK / 2), bbf + 8 * s);
        }
        cluster_arrive_relaxed(); cluster_wait();
      }
    }
  } else {
    reg_inc<232>();
    const int wg = __reduce_max_sync(0xffffffffu, ((unsigned)tid >> 7) - 1), wtid = tid & 127, warp = (tid >> 5) & 3, lane = tid & 31;
    const uint64_t da0 = mkdesc(sb + K4_A + wg * 8192, 16, 1024, 1);
    const uint64_t db0 = mkdesc(sb + K4_B, K4_STB / 3, 1024, 1);
    cluster_wait();
    const uint32_t rbe = map_cta(bbe, wtid & 1);
    bf16* hp = g_H + (size_t)(rb * 128 + wg * 64 + warp * 16 + (lane >> 2)) * FF + fs * 576 + (lane & 3) * 8;
    float acc[96]; uint32_t pk[48];
#pragma unroll
    for (int i = 0; i < 96; i++) acc[i] = 0.f;
    TLT(4, 1, 128); TLC(4, 3, 128);
    k4_tile<0>(acc, pk, da0, db0, ba, bbf, rbe, wtid, hp);
    k4_pack(acc, pk);
    k4_tile<1>(acc, pk, da0, db0, ba, bbf, rbe, wtid, hp);
    k4_pack(acc, pk);
    k4_tile<2>(acc, pk, da0, db0, ba, bbf, rbe, wtid, hp + 192);
    cluster_arrive_relaxed();
    TLT(4, 2, 128); TLC(4, 4, 128);
    k4_pack(acc, pk);
    k4_epi_n<0, 12>(pk, 1u, hp + 384);
    TLT(4, 7, 128);
    cluster_wait();
  }
}

constexpr int K5_NST = 4;
constexpr int K5_STAGE = 16384 + 36864;
constexpr int K5_GB = K5_NST * K5_STAGE, K5_BAR = K5_GB + 576, K5_SMEM = K5_BAR + 8 * (2 * K5_NST + 1);

template <int I> __device__ __forceinline__ float k5_acc(const float (&a)[128], const float (&b)[16]) { if constexpr (I < 128) return a[I]; else return b[I - 128]; }

template <int QD, int I>
__device__ __forceinline__ void k5_stage(const float (&a)[128], const float (&b)[16], uint32_t dst, uint32_t gbs) {
  if constexpr (I < 9) {
    constexpr int B = 9 * QD + I;
    const uint32_t gb = lds32(gbs + B * 16);
    const float g0 = bf_lo(gb), g1 = bf_hi(gb);
    sts32(dst + I * 16, pack_bf16(k5_acc<4 * B>(a, b) * g0, k5_acc<4 * B + 1>(a, b) * g1));
    sts32(dst + 8 * 144 + I * 16, pack_bf16(k5_acc<4 * B + 2>(a, b) * g0, k5_acc<4 * B + 3>(a, b) * g1));
    k5_stage<QD, I + 1>(a, b, dst, gbs);
  }
}
template <int QD>
__device__ __forceinline__ void k5_quarter(const float (&a)[128], const float (&b)[16], uint32_t sb, uint32_t dst, uint32_t gbs, int wg, int wtid,
                                           const CUtensorMap* tm, int col, int row) {
  k5_stage<QD, 0>(a, b, dst + QD * 18432, gbs);
  fence_async_smem();
  bar_sync(2 + wg, 128);
  if (wtid == 0) {
    asm volatile("cp.reduce.async.bulk.tensor.2d.global.shared::cta.add.tile.bulk_group [%0, {%2, %3}], [%1];"
                 :: "l"(tm), "r"(sb + QD * 18432 + wg * 9216), "r"(col + QD * 72), "r"(row) : "memory");
    bulk_commit();
  }
}

__global__ void __launch_bounds__(384, 1) k5_mlp2(const __grid_constant__ CUtensorMap tm_h, const __grid_constant__ CUtensorMap tm_w2,
                                                  const __grid_constant__ CUtensorMap tm_w2n, const __grid_constant__ CUtensorMap tm_out) {
  extern __shared__ __align__(1024) uint8_t smem[];
  const uint32_t sb = s2u(smem);
  const int tid = threadIdx.x, rb = blockIdx.x & 15, nh = (blockIdx.x >> 4) & 1, ks = blockIdx.x >> 5;
  const uint32_t bf = sb + K5_BAR, be = bf + 8 * K5_NST, bg = be + 8 * K5_NST;
  TL(5, 0);
  if (tid == 0) {
    for (int i = 0; i < K5_NST; i++) { mbar_init(bf + 8 * i, 1); mbar_init(be + 8 * i, 4); }
    mbar_init(bg, 1);
    fence_barrier_init();
    tmap_prefetch(&tm_h); tmap_prefetch(&tm_w2); tmap_prefetch(&tm_w2n); tmap_prefetch(&tm_out);
  }
  __syncthreads();
  cluster_arrive_relaxed(); cluster_wait();
  const int rank = cluster_rank();
  if (tid < 128) {
    reg_dec<40>();
    if (tid == 0) {
      auto load_b = [&](int st) {
        const int s = st % K5_NST;
        mbar_expect(bf + 8 * s, K5_STAGE);
        for (int g = 2 * rank; g < 2 * rank + 2; g++)
          tma5d_mc(sb + s * K5_STAGE + 16384 + g * 8192, &tm_w2, nh * 288 + g * 64, 0, 0, 0, (ks * 18 + st) * 2, bf + 8 * s);
        if (rank == 1) tma5d_mc(sb + s * K5_STAGE + 16384 + 32768, &tm_w2n, nh * 288 + 256, 0, 0, 0, (ks * 18 + st) * 2, bf + 8 * s);
      };
      load_b(0);
      pdl_wait();
      for (int st = 0; st < 18; st++) {
        const int s = st % K5_NST;
        if (st >= K5_NST) mbar_wait(be + 8 * s, (st / K5_NST - 1) & 1);
        if (st >= 1) load_b(st);
        tma2d(sb + s * K5_STAGE, &tm_h, (ks * 18 + st) * 64, rb * 128, bf + 8 * s);
        if (st == K5_NST) { mbar_expect(bg, 576); bulk_g2s(sb + K5_GB, g_mod + 5 * DM + nh * 288, 576, bg); }
      }
      cluster_arrive_relaxed(); cluster_wait();
    }
  } else {
    reg_inc<232>();
    const int ctid = tid - 128, wg = __reduce_max_sync(0xffffffffu, (unsigned)ctid >> 7), wtid = tid & 127, warp = (tid >> 5) & 3, lane = tid & 31, g = lane >> 2, q4 = lane & 3;
    float a[128], b[16];
#pragma unroll
    for (int i = 0; i < 128; i++) a[i] = 0.f;
#pragma unroll
    for (int i = 0; i < 16; i++) b[i] = 0.f;
    const uint64_t db0 = mkdesc(sb + 16384, 8192, 1024, 1);
    const uint64_t dn0 = mkdesc(sb + 16384 + 32768, 4096, 512, 2);
    const uint32_t rbe = map_cta(be, wtid & 1);
    uint32_t aoff[4];
    {
      const int r = wg * 64 + warp * 16 + (lane & 7) + ((lane >> 3) & 1) * 8;
#pragma unroll
      for (int j = 0; j < 4; j++) aoff[j] = sb + r * 128 + (((2 * j + (lane >> 4)) ^ (lane & 7)) << 4);
    }
    uint32_t A0[4][4], A1[4][4];
    auto step = [&](uint32_t (&A)[4][4], int st) {
      const int s = st % K5_NST;
      mbar_wait(bf + 8 * s, (st / K5_NST) & 1);
#pragma unroll
      for (int j = 0; j < 4; j++) ldsm4(A[j], aoff[j] + s * K5_STAGE);
      fence_regs(A[0]); fence_regs(A[1]); fence_regs(A[2]); fence_regs(A[3]);
      wg_fence();
#pragma unroll
      for (int j = 0; j < 4; j++) {
        wgmma_rs_n256_tb(a, A[j][0], A[j][1], A[j][2], A[j][3], db0 + (uint64_t)(s * (K5_STAGE / 16) + j * 128), 1);
        wgmma_rs_n32_tb(b, A[j][0], A[j][1], A[j][2], A[j][3], dn0 + (uint64_t)(s * (K5_STAGE / 16) + j * 64), 1);
      }
      wg_commit();
      if (st > 0) {
        wg_wait<1>();
        if (st - 1 + K5_NST < 18 && wtid < 2) mbar_arrive_remote(rbe + 8 * ((st - 1) % K5_NST));
      }
    };
#pragma unroll 1
    for (int st = 0; st < 18; st += 2) { step(A0, st); step(A1, st + 1); }
    wg_wait<0>();
    fence_regs(a); fence_regs(b);
    cluster_arrive_relaxed();
    TLT(5, 2, 128);
    mbar_wait(bg, 0);
    bar_sync(1, 256);
    const uint32_t dst = sb + (wg * 64 + warp * 16 + g) * 144 + q4 * 4, gbs = sb + K5_GB + q4 * 4;
    k5_quarter<0>(a, b, sb, dst, gbs, wg, wtid, &tm_out, nh * 288, rb * 128 + wg * 64);
    k5_quarter<1>(a, b, sb, dst, gbs, wg, wtid, &tm_out, nh * 288, rb * 128 + wg * 64);
    k5_quarter<2>(a, b, sb, dst, gbs, wg, wtid, &tm_out, nh * 288, rb * 128 + wg * 64);
    k5_quarter<3>(a, b, sb, dst, gbs, wg, wtid, &tm_out, nh * 288, rb * 128 + wg * 64);
    TLT(5, 3, 128);
    if (wtid == 0) bulk_wait_read();
    TLT(5, 7, 128);
    cluster_wait();
  }
}

}

typedef CUresult (*EncodeTiledFn)(CUtensorMap*, CUtensorMapDataType, cuuint32_t, void*, const cuuint64_t*, const cuuint64_t*, const cuuint32_t*,
                                  const cuuint32_t*, CUtensorMapInterleave, CUtensorMapSwizzle, CUtensorMapL2promotion, CUtensorMapFloatOOBfill);

static void make_map2d(EncodeTiledFn enc, CUtensorMap* m, const void* base, int cols, int rows, int box_cols, int box_rows, CUtensorMapSwizzle sw) {
  cuuint64_t dims[2] = {(cuuint64_t)cols, (cuuint64_t)rows};
  cuuint64_t strides[1] = {(cuuint64_t)cols * 2};
  cuuint32_t box[2] = {(cuuint32_t)box_cols, (cuuint32_t)box_rows};
  cuuint32_t es[2] = {1, 1};
  enc(m, CU_TENSOR_MAP_DATA_TYPE_BFLOAT16, 2, const_cast<void*>(base), dims, strides, box, es, CU_TENSOR_MAP_INTERLEAVE_NONE, sw,
      CU_TENSOR_MAP_L2_PROMOTION_L2_128B, CU_TENSOR_MAP_FLOAT_OOB_FILL_NONE);
}

template <typename... KArgs, typename... Args>
static void launch(void (*kern)(KArgs...), int grid, int block, int smem, bool pdl, int cluster, Args... args) {
  cudaLaunchConfig_t cfg = {};
  cfg.gridDim = dim3(grid); cfg.blockDim = dim3(block); cfg.dynamicSmemBytes = smem; cfg.stream = cudaStreamPerThread;
  cudaLaunchAttribute at[2];
  int n = 0;
  if (pdl) { at[n].id = cudaLaunchAttributeProgrammaticStreamSerialization; at[n].val.programmaticStreamSerializationAllowed = 1; n++; }
  if (cluster > 1) { at[n].id = cudaLaunchAttributeClusterDimension; at[n].val.clusterDim.x = cluster; at[n].val.clusterDim.y = 1; at[n].val.clusterDim.z = 1; n++; }
  cfg.attrs = at; cfg.numAttrs = n;
  cudaLaunchKernelEx(&cfg, kern, KArgs(args)...);
}

#define USE_PDL 1

extern "C" void kernel_launch(void* const* d_in, const int* in_sizes, int n_in, void* d_out, int out_size) {
  (void)in_sizes; (void)n_in; (void)out_size;
  const bf16* x    = (const bf16*)d_in[0];
  const bf16* wqkv = (const bf16*)d_in[1];
  const bf16* wo   = (const bf16*)d_in[2];
  const bf16* w1   = (const bf16*)d_in[4];
  const bf16* w2   = (const bf16*)d_in[5];
  const bf16* c    = (const bf16*)d_in[6];
  const bf16* wmod = (const bf16*)d_in[7];
  bf16* out = (bf16*)d_out;

  static EncodeTiledFn enc = nullptr;
  if (!enc) {
    void* fn = nullptr; cudaDriverEntryPointQueryResult qr;
    cudaGetDriverEntryPoint("cuTensorMapEncodeTiled", &fn, cudaEnableDefault, &qr);
    enc = (EncodeTiledFn)fn;
    cudaFuncSetAttribute(k1_qkv, cudaFuncAttributeMaxDynamicSharedMemorySize, K1_SMEM);
    cudaFuncSetAttribute(k2_attn, cudaFuncAttributeMaxDynamicSharedMemorySize, K2_SMEM);
    cudaFuncSetAttribute(k3_wo, cudaFuncAttributeMaxDynamicSharedMemorySize, K3_SMEM);
    cudaFuncSetAttribute(k4_mlp1, cudaFuncAttributeMaxDynamicSharedMemorySize, K4_SMEM);
    cudaFuncSetAttribute(k5_mlp2, cudaFuncAttributeMaxDynamicSharedMemorySize, K5_SMEM);
  }
  void *p_arena, *p_woT;
  cudaGetSymbolAddress(&p_arena, g_arena); cudaGetSymbolAddress(&p_woT, g_woT);
  void* p_h2 = p_arena;
  void* p_xn = (uint8_t*)p_arena + 96 * SLOT_BYTES;
  void* p_o = p_xn;
  void* p_H = (uint8_t*)p_arena + ACT_BYTES;
  CUtensorMap tm_xn, tm_wqkv, tm_o, tm_wo, tm_x, tm_x2s, tm_h2s, tm_h2, tm_w1, tm_H, tm_w2, tm_w2n, tm_out;
  make_map2d(enc, &tm_xn, p_xn, DM, SEQ, 64, 128, CU_TENSOR_MAP_SWIZZLE_128B);
  make_map2d(enc, &tm_wqkv, wqkv, 3 * DM, DM, 64, 32, CU_TENSOR_MAP_SWIZZLE_128B);
  make_map2d(enc, &tm_o, p_o, DM, SEQ, 64, 64, CU_TENSOR_MAP_SWIZZLE_128B);
  make_map2d(enc, &tm_x, x, DM, SEQ, 72, 128, CU_TENSOR_MAP_SWIZZLE_NONE);
  make_map2d(enc, &tm_x2s, out, DM, SEQ, 72, 128, CU_TENSOR_MAP_SWIZZLE_NONE);
  make_map2d(enc, &tm_out, out, DM, SEQ, 72, 64, CU_TENSOR_MAP_SWIZZLE_NONE);
  make_map2d(enc, &tm_h2s, p_h2, DM, SEQ, 72, 128, CU_TENSOR_MAP_SWIZZLE_NONE);
  make_map2d(enc, &tm_wo, p_woT, DM, DM, 64, 72, CU_TENSOR_MAP_SWIZZLE_128B);
  make_map2d(enc, &tm_h2, p_h2, DM, SEQ, 64, 128, CU_TENSOR_MAP_SWIZZLE_128B);
  make_map2d(enc, &tm_w1, w1, FF, DM, 64, K4_BK / 2, CU_TENSOR_MAP_SWIZZLE_128B);
  make_map2d(enc, &tm_H, p_H, FF, SEQ, 64, 128, CU_TENSOR_MAP_SWIZZLE_128B);
  for (int narrow = 0; narrow < 2; narrow++) {
    cuuint64_t dims[5] = {(cuuint64_t)DM, 2, 4, 4, (cuuint64_t)(FF / 32)};
    cuuint64_t strides[4] = {(cuuint64_t)DM * 2, (cuuint64_t)DM * 2 * 8, (cuuint64_t)DM * 2 * 2, (cuuint64_t)DM * 2 * 32};
    cuuint32_t box[5] = {narrow ? 32u : 64u, 2, 4, 4, 2};
    cuuint32_t es[5] = {1, 1, 1, 1, 1};
    enc(narrow ? &tm_w2n : &tm_w2, CU_TENSOR_MAP_DATA_TYPE_BFLOAT16, 5, const_cast<bf16*>(w2), dims, strides, box, es, CU_TENSOR_MAP_INTERLEAVE_NONE,
        narrow ? CU_TENSOR_MAP_SWIZZLE_64B : CU_TENSOR_MAP_SWIZZLE_128B, CU_TENSOR_MAP_L2_PROMOTION_L2_128B, CU_TENSOR_MAP_FLOAT_OOB_FILL_NONE);
  }
  launch(k0_mod_ln, 128, 256, 0, false, 1, x, c, wmod);
  launch(k1_qkv, 132, 320, K1_SMEM, USE_PDL, 2, tm_xn, tm_wqkv, wo);
  launch(k2_attn, 132, 512, K2_SMEM, USE_PDL, 1, c, wmod, w1, w2);
  launch(k3_wo, 128, 288, K3_SMEM, USE_PDL, 2, tm_o, tm_wo, tm_x, tm_x2s, tm_h2s);
  launch(k4_mlp1, 128, 384, K4_SMEM, USE_PDL, 2, tm_h2, tm_w1);
  launch(k5_mlp2, 128, 384, K5_SMEM, USE_PDL, 2, tm_H, tm_w2, tm_w2n, tm_out);
}
```

```cpp
#include <cuda_runtime.h>
#include <cuda_bf16.h>
#include <cuda.h>
#include <stdint.h>

namespace {

constexpr int SEQ = 2048, DM = 576, DHEAD = 18, FF = 4608;
constexpr int SLOT_BYTES = SEQ * 48;

typedef __nv_bfloat16 bf16;

__device__ __align__(1024) bf16    g_mod[6 * DM];
#define MODP 2
__device__ __align__(1024) float   g_modp[MODP * 2 * DM];
constexpr int ACT_BYTES = SEQ * DM * 2;
__device__ __align__(1024) uint8_t g_arena[ACT_BYTES + SEQ * FF * 2];
#define g_qkvp (g_arena)
#define g_h2   (reinterpret_cast<bf16*>(g_arena))
#define g_xn   (reinterpret_cast<bf16*>(g_arena + 96 * SLOT_BYTES))
#define g_o    (reinterpret_cast<bf16*>(g_arena + 96 * SLOT_BYTES))
#define g_H    (reinterpret_cast<bf16*>(g_arena + ACT_BYTES))
__device__ __align__(1024) float   g_nrm[16 * 64];
__device__ __align__(1024) bf16    g_woT[DM * DM];
__device__ __align__(1024) uint4   g_stats[SEQ * 8];
__device__ unsigned int g_epoch;

__device__ __forceinline__ uint32_t s2u(const void* p) { return (uint32_t)__cvta_generic_to_shared(p); }
__device__ __forceinline__ void mbar_init(uint32_t b, uint32_t c) { asm volatile("mbarrier.init.shared::cta.b64 [%0], %1;" :: "r"(b), "r"(c) : "memory"); }
__device__ __forceinline__ void mbar_expect(uint32_t b, uint32_t bytes) { asm volatile("mbarrier.arrive.expect_tx.shared::cta.b64 _, [%0], %1;" :: "r"(b), "r"(bytes) : "memory"); }
__device__ __forceinline__ void mbar_arrive(uint32_t b) { asm volatile("mbarrier.arrive.shared::cta.b64 _, [%0];" :: "r"(b) : "memory"); }
__device__ __forceinline__ bool mbar_try(uint32_t b, uint32_t ph) {
  uint32_t ok;
  asm volatile("{\n.reg .pred p;\nmbarrier.try_wait.parity.shared::cta.b64 p, [%1], %2;\nselp.u32 %0, 1, 0, p;\n}" : "=r"(ok) : "r"(b), "r"(ph) : "memory");
  return ok != 0;
}
__device__ __forceinline__ void mbar_wait(uint32_t b, uint32_t ph) {
  if (!mbar_try(b, ph)) {
    for (int n = 0; n < (1 << 22); n++) if (mbar_try(b, ph)) break;
  }
}
__device__ __forceinline__ void fence_barrier_init() { asm volatile("fence.mbarrier_init.release.cluster;" ::: "memory"); }
__device__ __forceinline__ void fence_async_smem() { asm volatile("fence.proxy.async.shared::cta;" ::: "memory"); }
__device__ __forceinline__ void bar_sync(int id, int n) { asm volatile("bar.sync %0, %1;" :: "r"(id), "r"(n) : "memory"); }
__device__ __forceinline__ void pdl_wait() { asm volatile("griddepcontrol.wait;" ::: "memory"); }
__device__ __forceinline__ void pdl_launch() { asm volatile("griddepcontrol.launch_dependents;" ::: "memory"); }
__device__ __forceinline__ void bulk_g2s(uint32_t dst, const void* src, uint32_t bytes, uint32_t bar) {
  asm volatile("cp.async.bulk.shared::cluster.global.mbarrier::complete_tx::bytes [%0], [%1], %2, [%3];" :: "r"(dst), "l"(src), "r"(bytes), "r"(bar) : "memory");
}
__device__ __forceinline__ void bulk_s2g(void* dst, uint32_t src, uint32_t bytes) {
  asm volatile("cp.async.bulk.global.shared::cta.bulk_group [%0], [%1], %2;" :: "l"(dst), "r"(src), "r"(bytes) : "memory");
}
__device__ __forceinline__ void bulk_commit() { asm volatile("cp.async.bulk.commit_group;" ::: "memory"); }
__device__ __forceinline__ void bulk_wait_read() { asm volatile("cp.async.bulk.wait_group.read 0;" ::: "memory"); }
__device__ __forceinline__ void tma2d(uint32_t dst, const CUtensorMap* m, int x, int y, uint32_t bar) {
  asm volatile("cp.async.bulk.tensor.2d.shared::cluster.global.mbarrier::complete_tx::bytes [%0], [%1, {%3, %4}], [%2];"
               :: "r"(dst), "l"(m), "r"(bar), "r"(x), "r"(y) : "memory");
}
__device__ __forceinline__ void tma2d_mc(uint32_t dst, const CUtensorMap* m, int x, int y, uint32_t bar) {
  asm volatile("cp.async.bulk.tensor.2d.shared::cluster.global.mbarrier::complete_tx::bytes.multicast::cluster [%0], [%1, {%3, %4}], [%2], %5;"
               :: "r"(dst), "l"(m), "r"(bar), "r"(x), "r"(y), "h"((uint16_t)3) : "memory");
}
__device__ __forceinline__ void tma5d_mc(uint32_t dst, const CUtensorMap* m, int c0, int c1, int c2, int c3, int c4, uint32_t bar) {
  asm volatile("cp.async.bulk.tensor.5d.shared::cluster.global.mbarrier::complete_tx::bytes.multicast::cluster [%0], [%1, {%3, %4, %5, %6, %7}], [%2], %8;"
               :: "r"(dst), "l"(m), "r"(bar), "r"(c0), "r"(c1), "r"(c2), "r"(c3), "r"(c4), "h"((uint16_t)3) : "memory");
}
__device__ __forceinline__ void tma2d_store(const CUtensorMap* m, uint32_t src, int x, int y) {
  asm volatile("cp.async.bulk.tensor.2d.global.shared::cta.bulk_group [%0, {%2, %3}], [%1];" :: "l"(m), "r"(src), "r"(x), "r"(y) : "memory");
}
__device__ __forceinline__ uint32_t map_cta(uint32_t a, uint32_t cta) { uint32_t r; asm("mapa.shared::cluster.u32 %0, %1, %2;" : "=r"(r) : "r"(a), "r"(cta)); return r; }
__device__ __forceinline__ void mbar_arrive_remote(uint32_t ra) { asm volatile("mbarrier.arrive.shared::cluster.b64 _, [%0];" :: "r"(ra) : "memory"); }
__device__ __forceinline__ void cluster_arrive_relaxed() { asm volatile("barrier.cluster.arrive.relaxed;" ::: "memory"); }
__device__ __forceinline__ void cluster_wait() { asm volatile("barrier.cluster.wait.acquire;" ::: "memory"); }
__device__ __forceinline__ uint32_t cluster_rank() { uint32_t r; asm("mov.u32 %0, %%cluster_ctarank;" : "=r"(r)); return r; }
__device__ __forceinline__ void tma2d_prefetch(const CUtensorMap* m, int x, int y) {
  asm volatile("cp.async.bulk.prefetch.tensor.2d.L2.global [%0, {%1, %2}];" :: "l"(m), "r"(x), "r"(y) : "memory");
}
__device__ __forceinline__ void tmap_prefetch(const CUtensorMap* m) { asm volatile("prefetch.tensormap [%0];" :: "l"(m) : "memory"); }
__device__ __forceinline__ void wg_fence() { asm volatile("wgmma.fence.sync.aligned;" ::: "memory"); }
__device__ __forceinline__ void wg_commit() { asm volatile("wgmma.commit_group.sync.aligned;" ::: "memory"); }
template <int N> __device__ __forceinline__ void wg_wait() { asm volatile("wgmma.wait_group.sync.aligned %0;" :: "n"(N) : "memory"); }
__device__ __forceinline__ uint64_t mkdesc(uint32_t addr, uint32_t lbo, uint32_t sbo, int sw) {
  return (uint64_t)((addr & 0x3FFFF) >> 4) | ((uint64_t)(lbo >> 4) << 16) | ((uint64_t)(sbo >> 4) << 32) | ((uint64_t)sw << 62);
}
template <int N> __device__ __forceinline__ void fence_regs(float (&d)[N]) {
#pragma unroll
  for (int i = 0; i < N; i++) asm volatile("" : "+f"(d[i]) :: "memory");
}
template <int N> __device__ __forceinline__ void fence_regs(uint32_t (&d)[N]) {
#pragma unroll
  for (int i = 0; i < N; i++) asm volatile("" : "+r"(d[i]) :: "memory");
}
__device__ __forceinline__ float ex2(float x) { float y; asm("ex2.approx.ftz.f32 %0, %1;" : "=f"(y) : "f"(x)); return y; }
__device__ __forceinline__ float tanh_fast(float x) { float y; asm("tanh.approx.f32 %0, %1;" : "=f"(y) : "f"(x)); return y; }
__device__ __forceinline__ uint32_t pack_bf16(float lo, float hi) { uint32_t v; asm("cvt.rn.bf16x2.f32 %0, %1, %2;" : "=r"(v) : "f"(hi), "f"(lo)); return v; }
__device__ __forceinline__ float bf_lo(uint32_t v) { return __uint_as_float(v << 16); }
__device__ __forceinline__ float bf_hi(uint32_t v) { return __uint_as_float(v & 0xFFFF0000u); }
__device__ __forceinline__ float bf_round(float x) { return __bfloat162float(__float2bfloat16_rn(x)); }
__device__ __forceinline__ uint32_t hfma2(uint32_t a, uint32_t b, uint32_t c) { uint32_t d; asm("fma.rn.bf16x2 %0, %1, %2, %3;" : "=r"(d) : "r"(a), "r"(b), "r"(c)); return d; }
__device__ __forceinline__ uint32_t hadd2(uint32_t a, uint32_t b) { uint32_t d; asm("add.rn.bf16x2 %0, %1, %2;" : "=r"(d) : "r"(a), "r"(b)); return d; }
__device__ __forceinline__ uint32_t opaque(uint32_t v) { uint32_t r; asm volatile("mov.b32 %0, %1;" : "=r"(r) : "r"(v)); return r; }
__device__ __forceinline__ void ldsm4(uint32_t (&r)[4], uint32_t a) {
  asm volatile("ldmatrix.sync.aligned.m8n8.x4.shared.b16 {%0,%1,%2,%3}, [%4];" : "=r"(r[0]), "=r"(r[1]), "=r"(r[2]), "=r"(r[3]) : "r"(a));
}
__device__ __forceinline__ uint4 lds128(uint32_t a) { uint4 v; asm volatile("ld.shared.v4.b32 {%0,%1,%2,%3}, [%4];" : "=r"(v.x), "=r"(v.y), "=r"(v.z), "=r"(v.w) : "r"(a)); return v; }
__device__ __forceinline__ uint32_t lds32(uint32_t a) { uint32_t v; asm volatile("ld.shared.b32 %0, [%1];" : "=r"(v) : "r"(a)); return v; }
__device__ __forceinline__ void sts32(uint32_t a, uint32_t v) { asm volatile("st.shared.b32 [%0], %1;" :: "r"(a), "r"(v) : "memory"); }
template <int R> __device__ __forceinline__ void reg_inc() { asm volatile("setmaxnreg.inc.sync.aligned.u32 %0;" :: "n"(R)); }
template <int R> __device__ __forceinline__ void reg_dec() { asm volatile("setmaxnreg.dec.sync.aligned.u32 %0;" :: "n"(R)); }

#define TL(k, i)
#define TLT(k, i, t)
#define TLC(k, i, t)

__device__ __forceinline__ void wgmma_rs_n216_tb(float (&d)[108], uint32_t a0, uint32_t a1, uint32_t a2, uint32_t a3, uint64_t db, int sd) {
  asm volatile("{\n.reg .pred p;\nsetp.ne.b32 p, %113, 0;\n"
    "wgmma.mma_async.sync.aligned.m64n216k16.f32.bf16.bf16 "
    "{%0, %1, %2, %3, %4, %5, %6, %7, %8, %9, %10, %11, %12, %13, %14, %15, %16, %17, %18, %19, %20, %21, %22, %23, %24, %25, %26, %27, %28, %29, %30, %31, %32, %33, %34, %35, %36, %37, %38, %39, %40, %41, %42, %43, %44, %45, %46, %47, %48, %49, %50, %51, %52, %53, %54, %55, %56, %57, %58, %59, %60, %61, %62, %63, %64, %65, %66, %67, %68, %69, %70, %71, %72, %73, %74, %75, %76, %77, %78, %79, %80, %81, %82, %83, %84, %85, %86, %87, %88, %89, %90, %91, %92, %93, %94, %95, %96, %97, %98, %99, %100, %101, %102, %103, %104, %105, %106, %107}, {%108,%109,%110,%111}, %112, p, 1, 1, 1;\n}\n"
    : "+f"(d[0]), "+f"(d[1]), "+f"(d[2]), "+f"(d[3]), "+f"(d[4]), "+f"(d[5]), "+f"(d[6]), "+f"(d[7]), "+f"(d[8]), "+f"(d[9]), "+f"(d[10]), "+f"(d[11]), "+f"(d[12]), "+f"(d[13]), "+f"(d[14]), "+f"(d[15]), "+f"(d[16]), "+f"(d[17]), "+f"(d[18]), "+f"(d[19]), "+f"(d[20]), "+f"(d[21]), "+f"(d[22]), "+f"(d[23]), "+f"(d[24]), "+f"(d[25]), "+f"(d[26]), "+f"(d[27]), "+f"(d[28]), "+f"(d[29]), "+f"(d[30]), "+f"(d[31]), "+f"(d[32]), "+f"(d[33]), "+f"(d[34]), "+f"(d[35]), "+f"(d[36]), "+f"(d[37]), "+f"(d[38]), "+f"(d[39]), "+f"(d[40]), "+f"(d[41]), "+f"(d[42]), "+f"(d[43]), "+f"(d[44]), "+f"(d[45]), "+f"(d[46]), "+f"(d[47]), "+f"(d[48]), "+f"(d[49]), "+f"(d[50]), "+f"(d[51]), "+f"(d[52]), "+f"(d[53]), "+f"(d[54]), "+f"(d[55]), "+f"(d[56]), "+f"(d[57]), "+f"(d[58]), "+f"(d[59]), "+f"(d[60]), "+f"(d[61]), "+f"(d[62]), "+f"(d[63]), "+f"(d[64]), "+f"(d[65]), "+f"(d[66]), "+f"(d[67]), "+f"(d[68]), "+f"(d[69]), "+f"(d[70]), "+f"(d[71]), "+f"(d[72]), "+f"(d[73]), "+f"(d[74]), "+f"(d[75]), "+f"(d[76]), "+f"(d[77]), "+f"(d[78]), "+f"(d[79]), "+f"(d[80]), "+f"(d[81]), "+f"(d[82]), "+f"(d[83]), "+f"(d[84]), "+f"(d[85]), "+f"(d[86]), "+f"(d[87]), "+f"(d[88]), "+f"(d[89]), "+f"(d[90]), "+f"(d[91]), "+f"(d[92]), "+f"(d[93]), "+f"(d[94]), "+f"(d[95]), "+f"(d[96]), "+f"(d[97]), "+f"(d[98]), "+f"(d[99]), "+f"(d[100]), "+f"(d[101]), "+f"(d[102]), "+f"(d[103]), "+f"(d[104]), "+f"(d[105]), "+f"(d[106]), "+f"(d[107])
    : "r"(a0), "r"(a1), "r"(a2), "r"(a3), "l"(db), "r"(sd));
}
__device__ __forceinline__ void wgmma_ss_n72(float (&d)[36], uint64_t da, uint64_t db, int sd) {
  asm volatile("{\n.reg .pred p;\nsetp.ne.b32 p, %38, 0;\n"
    "wgmma.mma_async.sync.aligned.m64n72k16.f32.bf16.bf16 "
    "{%0, %1, %2, %3, %4, %5, %6, %7, %8, %9, %10, %11, %12, %13, %14, %15, %16, %17, %18, %19, %20, %21, %22, %23, %24, %25, %26, %27, %28, %29, %30, %31, %32, %33, %34, %35}, %36, %37, p, 1, 1, 0, 0;\n}\n"
    : "+f"(d[0]), "+f"(d[1]), "+f"(d[2]), "+f"(d[3]), "+f"(d[4]), "+f"(d[5]), "+f"(d[6]), "+f"(d[7]), "+f"(d[8]), "+f"(d[9]), "+f"(d[10]), "+f"(d[11]), "+f"(d[12]), "+f"(d[13]), "+f"(d[14]), "+f"(d[15]), "+f"(d[16]), "+f"(d[17]), "+f"(d[18]), "+f"(d[19]), "+f"(d[20]), "+f"(d[21]), "+f"(d[22]), "+f"(d[23]), "+f"(d[24]), "+f"(d[25]), "+f"(d[26]), "+f"(d[27]), "+f"(d[28]), "+f"(d[29]), "+f"(d[30]), "+f"(d[31]), "+f"(d[32]), "+f"(d[33]), "+f"(d[34]), "+f"(d[35])
    : "l"(da), "l"(db), "r"(sd));
}
__device__ __forceinline__ void wgmma_ss_n192_tb(float (&d)[96], uint64_t da, uint64_t db, int sd) {
  asm volatile("{\n.reg .pred p;\nsetp.ne.b32 p, %98, 0;\n"
    "wgmma.mma_async.sync.aligned.m64n192k16.f32.bf16.bf16 "
    "{%0, %1, %2, %3, %4, %5, %6, %7, %8, %9, %10, %11, %12, %13, %14, %15, %16, %17, %18, %19, %20, %21, %22, %23, %24, %25, %26, %27, %28, %29, %30, %31, %32, %33, %34, %35, %36, %37, %38, %39, %40, %41, %42, %43, %44, %45, %46, %47, %48, %49, %50, %51, %52, %53, %54, %55, %56, %57, %58, %59, %60, %61, %62, %63, %64, %65, %66, %67, %68, %69, %70, %71, %72, %73, %74, %75, %76, %77, %78, %79, %80, %81, %82, %83, %84, %85, %86, %87, %88, %89, %90, %91, %92, %93, %94, %95}, %96, %97, p, 1, 1, 0, 1;\n}\n"
    : "+f"(d[0]), "+f"(d[1]), "+f"(d[2]), "+f"(d[3]), "+f"(d[4]), "+f"(d[5]), "+f"(d[6]), "+f"(d[7]), "+f"(d[8]), "+f"(d[9]), "+f"(d[10]), "+f"(d[11]), "+f"(d[12]), "+f"(d[13]), "+f"(d[14]), "+f"(d[15]), "+f"(d[16]), "+f"(d[17]), "+f"(d[18]), "+f"(d[19]), "+f"(d[20]), "+f"(d[21]), "+f"(d[22]), "+f"(d[23]), "+f"(d[24]), "+f"(d[25]), "+f"(d[26]), "+f"(d[27]), "+f"(d[28]), "+f"(d[29]), "+f"(d[30]), "+f"(d[31]), "+f"(d[32]), "+f"(d[33]), "+f"(d[34]), "+f"(d[35]), "+f"(d[36]), "+f"(d[37]), "+f"(d[38]), "+f"(d[39]), "+f"(d[40]), "+f"(d[41]), "+f"(d[42]), "+f"(d[43]), "+f"(d[44]), "+f"(d[45]), "+f"(d[46]), "+f"(d[47]), "+f"(d[48]), "+f"(d[49]), "+f"(d[50]), "+f"(d[51]), "+f"(d[52]), "+f"(d[53]), "+f"(d[54]), "+f"(d[55]), "+f"(d[56]), "+f"(d[57]), "+f"(d[58]), "+f"(d[59]), "+f"(d[60]), "+f"(d[61]), "+f"(d[62]), "+f"(d[63]), "+f"(d[64]), "+f"(d[65]), "+f"(d[66]), "+f"(d[67]), "+f"(d[68]), "+f"(d[69]), "+f"(d[70]), "+f"(d[71]), "+f"(d[72]), "+f"(d[73]), "+f"(d[74]), "+f"(d[75]), "+f"(d[76]), "+f"(d[77]), "+f"(d[78]), "+f"(d[79]), "+f"(d[80]), "+f"(d[81]), "+f"(d[82]), "+f"(d[83]), "+f"(d[84]), "+f"(d[85]), "+f"(d[86]), "+f"(d[87]), "+f"(d[88]), "+f"(d[89]), "+f"(d[90]), "+f"(d[91]), "+f"(d[92]), "+f"(d[93]), "+f"(d[94]), "+f"(d[95])
    : "l"(da), "l"(db), "r"(sd));
}
__device__ __forceinline__ void wgmma_rs_n256_tb(float (&d)[128], uint32_t a0, uint32_t a1, uint32_t a2, uint32_t a3, uint64_t db, int sd) {
  asm volatile("{\n.reg .pred p;\nsetp.ne.b32 p, %133, 0;\n"
    "wgmma.mma_async.sync.aligned.m64n256k16.f32.bf16.bf16 "
    "{%0, %1, %2, %3, %4, %5, %6, %7, %8, %9, %10, %11, %12, %13, %14, %15, %16, %17, %18, %19, %20, %21, %22, %23, %24, %25, %26, %27, %28, %29, %30, %31, %32, %33, %34, %35, %36, %37, %38, %39, %40, %41, %42, %43, %44, %45, %46, %47, %48, %49, %50, %51, %52, %53, %54, %55, %56, %57, %58, %59, %60, %61, %62, %63, %64, %65, %66, %67, %68, %69, %70, %71, %72, %73, %74, %75, %76, %77, %78, %79, %80, %81, %82, %83, %84, %85, %86, %87, %88, %89, %90, %91, %92, %93, %94, %95, %96, %97, %98, %99, %100, %101, %102, %103, %104, %105, %106, %107, %108, %109, %110, %111, %112, %113, %114, %115, %116, %117, %118, %119, %120, %121, %122, %123, %124, %125, %126, %127}, {%128,%129,%130,%131}, %132, p, 1, 1, 1;\n}\n"
    : "+f"(d[0]), "+f"(d[1]), "+f"(d[2]), "+f"(d[3]), "+f"(d[4]), "+f"(d[5]), "+f"(d[6]), "+f"(d[7]), "+f"(d[8]), "+f"(d[9]), "+f"(d[10]), "+f"(d[11]), "+f"(d[12]), "+f"(d[13]), "+f"(d[14]), "+f"(d[15]), "+f"(d[16]), "+f"(d[17]), "+f"(d[18]), "+f"(d[19]), "+f"(d[20]), "+f"(d[21]), "+f"(d[22]), "+f"(d[23]), "+f"(d[24]), "+f"(d[25]), "+f"(d[26]), "+f"(d[27]), "+f"(d[28]), "+f"(d[29]), "+f"(d[30]), "+f"(d[31]), "+f"(d[32]), "+f"(d[33]), "+f"(d[34]), "+f"(d[35]), "+f"(d[36]), "+f"(d[37]), "+f"(d[38]), "+f"(d[39]), "+f"(d[40]), "+f"(d[41]), "+f"(d[42]), "+f"(d[43]), "+f"(d[44]), "+f"(d[45]), "+f"(d[46]), "+f"(d[47]), "+f"(d[48]), "+f"(d[49]), "+f"(d[50]), "+f"(d[51]), "+f"(d[52]), "+f"(d[53]), "+f"(d[54]), "+f"(d[55]), "+f"(d[56]), "+f"(d[57]), "+f"(d[58]), "+f"(d[59]), "+f"(d[60]), "+f"(d[61]), "+f"(d[62]), "+f"(d[63]), "+f"(d[64]), "+f"(d[65]), "+f"(d[66]), "+f"(d[67]), "+f"(d[68]), "+f"(d[69]), "+f"(d[70]), "+f"(d[71]), "+f"(d[72]), "+f"(d[73]), "+f"(d[74]), "+f"(d[75]), "+f"(d[76]), "+f"(d[77]), "+f"(d[78]), "+f"(d[79]), "+f"(d[80]), "+f"(d[81]), "+f"(d[82]), "+f"(d[83]), "+f"(d[84]), "+f"(d[85]), "+f"(d[86]), "+f"(d[87]), "+f"(d[88]), "+f"(d[89]), "+f"(d[90]), "+f"(d[91]), "+f"(d[92]), "+f"(d[93]), "+f"(d[94]), "+f"(d[95]), "+f"(d[96]), "+f"(d[97]), "+f"(d[98]), "+f"(d[99]), "+f"(d[100]), "+f"(d[101]), "+f"(d[102]), "+f"(d[103]), "+f"(d[104]), "+f"(d[105]), "+f"(d[106]), "+f"(d[107]), "+f"(d[108]), "+f"(d[109]), "+f"(d[110]), "+f"(d[111]), "+f"(d[112]), "+f"(d[113]), "+f"(d[114]), "+f"(d[115]), "+f"(d[116]), "+f"(d[117]), "+f"(d[118]), "+f"(d[119]), "+f"(d[120]), "+f"(d[121]), "+f"(d[122]), "+f"(d[123]), "+f"(d[124]), "+f"(d[125]), "+f"(d[126]), "+f"(d[127])
    : "r"(a0), "r"(a1), "r"(a2), "r"(a3), "l"(db), "r"(sd));
}
__device__ __forceinline__ void wgmma_rs_n32_tb(float (&d)[16], uint32_t a0, uint32_t a1, uint32_t a2, uint32_t a3, uint64_t db, int sd) {
  asm volatile("{\n.reg .pred p;\nsetp.ne.b32 p, %21, 0;\n"
    "wgmma.mma_async.sync.aligned.m64n32k16.f32.bf16.bf16 "
    "{%0, %1, %2, %3, %4, %5, %6, %7, %8, %9, %10, %11, %12, %13, %14, %15}, {%16,%17,%18,%19}, %20, p, 1, 1, 1;\n}\n"
    : "+f"(d[0]), "+f"(d[1]), "+f"(d[2]), "+f"(d[3]), "+f"(d[4]), "+f"(d[5]), "+f"(d[6]), "+f"(d[7]), "+f"(d[8]), "+f"(d[9]), "+f"(d[10]), "+f"(d[11]), "+f"(d[12]), "+f"(d[13]), "+f"(d[14]), "+f"(d[15])
    : "r"(a0), "r"(a1), "r"(a2), "r"(a3), "l"(db), "r"(sd));
}
__device__ __forceinline__ void wgmma_rs_n64(float (&d)[32], uint32_t a0, uint32_t a1, uint32_t a2, uint32_t a3, uint64_t db, int sd) {
  asm volatile("{\n.reg .pred p;\nsetp.ne.b32 p, %37, 0;\n"
    "wgmma.mma_async.sync.aligned.m64n64k16.f32.bf16.bf16 "
    "{%0, %1, %2, %3, %4, %5, %6, %7, %8, %9, %10, %11, %12, %13, %14, %15, %16, %17, %18, %19, %20, %21, %22, %23, %24, %25, %26, %27, %28, %29, %30, %31}, {%32,%33,%34,%35}, %36, p, 1, 1, 0;\n}\n"
    : "+f"(d[0]), "+f"(d[1]), "+f"(d[2]), "+f"(d[3]), "+f"(d[4]), "+f"(d[5]), "+f"(d[6]), "+f"(d[7]), "+f"(d[8]), "+f"(d[9]), "+f"(d[10]), "+f"(d[11]), "+f"(d[12]), "+f"(d[13]), "+f"(d[14]), "+f"(d[15]), "+f"(d[16]), "+f"(d[17]), "+f"(d[18]), "+f"(d[19]), "+f"(d[20]), "+f"(d[21]), "+f"(d[22]), "+f"(d[23]), "+f"(d[24]), "+f"(d[25]), "+f"(d[26]), "+f"(d[27]), "+f"(d[28]), "+f"(d[29]), "+f"(d[30]), "+f"(d[31])
    : "r"(a0), "r"(a1), "r"(a2), "r"(a3), "l"(db), "r"(sd));
}
__device__ __forceinline__ void wgmma_rs0_n64(float (&d)[32], uint32_t a0, uint32_t a1, uint32_t a2, uint32_t a3, uint64_t db) {
  asm volatile("{\n.reg .pred p;\nsetp.ne.b32 p, 0, 0;\n"
    "wgmma.mma_async.sync.aligned.m64n64k16.f32.bf16.bf16 "
    "{%0, %1, %2, %3, %4, %5, %6, %7, %8, %9, %10, %11, %12, %13, %14, %15, %16, %17, %18, %19, %20, %21, %22, %23, %24, %25, %26, %27, %28, %29, %30, %31}, {%32,%33,%34,%35}, %36, p, 1, 1, 0;\n}\n"
    : "=f"(d[0]), "=f"(d[1]), "=f"(d[2]), "=f"(d[3]), "=f"(d[4]), "=f"(d[5]), "=f"(d[6]), "=f"(d[7]), "=f"(d[8]), "=f"(d[9]), "=f"(d[10]), "=f"(d[11]), "=f"(d[12]), "=f"(d[13]), "=f"(d[14]), "=f"(d[15]), "=f"(d[16]), "=f"(d[17]), "=f"(d[18]), "=f"(d[19]), "=f"(d[20]), "=f"(d[21]), "=f"(d[22]), "=f"(d[23]), "=f"(d[24]), "=f"(d[25]), "=f"(d[26]), "=f"(d[27]), "=f"(d[28]), "=f"(d[29]), "=f"(d[30]), "=f"(d[31])
    : "r"(a0), "r"(a1), "r"(a2), "r"(a3), "l"(db));
}
__device__ __forceinline__ void wgmma_rs_n24_tb(float (&d)[12], uint32_t a0, uint32_t a1, uint32_t a2, uint32_t a3, uint64_t db, int sd) {
  asm volatile("{\n.reg .pred p;\nsetp.ne.b32 p, %17, 0;\n"
    "wgmma.mma_async.sync.aligned.m64n24k16.f32.bf16.bf16 "
    "{%0, %1, %2, %3, %4, %5, %6, %7, %8, %9, %10, %11}, {%12,%13,%14,%15}, %16, p, 1, 1, 1;\n}\n"
    : "+f"(d[0]), "+f"(d[1]), "+f"(d[2]), "+f"(d[3]), "+f"(d[4]), "+f"(d[5]), "+f"(d[6]), "+f"(d[7]), "+f"(d[8]), "+f"(d[9]), "+f"(d[10]), "+f"(d[11])
    : "r"(a0), "r"(a1), "r"(a2), "r"(a3), "l"(db), "r"(sd));
}

__device__ __forceinline__ float silu_ref(float c) { return bf_round(c / (1.0f + __expf(-c))); }

__global__ void __launch_bounds__(256) k0_mod_ln(const bf16* __restrict__ x, const bf16* __restrict__ c, const bf16* __restrict__ wmod) {
  __shared__ float red[8][32];
  pdl_launch();
  const int t = threadIdx.x, warp = t >> 5, lane = t & 31;
  if (blockIdx.x < 36 * MODP) {
    constexpr int ROWS = DM / MODP, NJ = (ROWS + 63) / 64;
    const int b = blockIdx.x, strip = b % 36, half = b / 36, cq = t & 3, kr = t >> 2;
    if (b == 0 && t == 0) g_epoch = g_epoch + 1;
    uint4 wv[NJ]; float cs[NJ];
#pragma unroll
    for (int j = 0; j < NJ; j++) {
      const int kk = kr + 64 * j, k = half * ROWS + kk;
      if (kk < ROWS) { wv[j] = __ldg(reinterpret_cast<const uint4*>(wmod + (size_t)k * (6 * DM) + strip * 32 + cq * 8)); cs[j] = __bfloat162float(c[k]); }
      else { wv[j] = make_uint4(0, 0, 0, 0); cs[j] = 0.f; }
    }
    float acc[8];
#pragma unroll
    for (int i = 0; i < 8; i++) acc[i] = 0.f;
#pragma unroll
    for (int j = 0; j < NJ; j++) {
      const float s = silu_ref(cs[j]);
      const uint32_t w[4] = {wv[j].x, wv[j].y, wv[j].z, wv[j].w};
#pragma unroll
      for (int i = 0; i < 4; i++) { acc[2 * i] = fmaf(s, bf_lo(w[i]), acc[2 * i]); acc[2 * i + 1] = fmaf(s, bf_hi(w[i]), acc[2 * i + 1]); }
    }
#pragma unroll
    for (int o = 4; o < 32; o <<= 1) {
#pragma unroll
      for (int i = 0; i < 8; i++) acc[i] += __shfl_xor_sync(0xffffffffu, acc[i], o);
    }
    if (lane < 4) {
#pragma unroll
      for (int i = 0; i < 8; i++) red[warp][lane * 8 + i] = acc[i];
    }
    __syncthreads();
    if (t < 32) {
      float s = 0.f;
#pragma unroll
      for (int w = 0; w < 8; w++) s += red[w][t];
      g_modp[half * 1152 + strip * 32 + t] = s;
    }
  } else {
    const int r0 = (blockIdx.x - 36 * MODP) * 16 + warp * 2;
    const uint32_t* xr = reinterpret_cast<const uint32_t*>(x + (size_t)r0 * DM);
    uint32_t xv[2][9];
#pragma unroll
    for (int j = 0; j < 9; j++) { xv[0][j] = __ldg(xr + lane + 32 * j); xv[1][j] = __ldg(xr + 288 + lane + 32 * j); }
    float s0 = 0.f, s1 = 0.f;
#pragma unroll
    for (int j = 0; j < 9; j++) { s0 += bf_lo(xv[0][j]) + bf_hi(xv[0][j]); s1 += bf_lo(xv[1][j]) + bf_hi(xv[1][j]); }
#pragma unroll
    for (int o = 16; o; o >>= 1) { s0 += __shfl_xor_sync(0xffffffffu, s0, o); s1 += __shfl_xor_sync(0xffffffffu, s1, o); }
    const float m0 = s0 * (1.0f / DM), m1 = s1 * (1.0f / DM);
    float v0 = 0.f, v1 = 0.f;
#pragma unroll
    for (int j = 0; j < 9; j++) {
      float d;
      d = bf_lo(xv[0][j]) - m0; v0 = fmaf(d, d, v0); d = bf_hi(xv[0][j]) - m0; v0 = fmaf(d, d, v0);
      d = bf_lo(xv[1][j]) - m1; v1 = fmaf(d, d, v1); d = bf_hi(xv[1][j]) - m1; v1 = fmaf(d, d, v1);
    }
#pragma unroll
    for (int o = 16; o; o >>= 1) { v0 += __shfl_xor_sync(0xffffffffu, v0, o); v1 += __shfl_xor_sync(0xffffffffu, v1, o); }
    const float rs0 = 1.0f / sqrtf(v0 * (1.0f / DM) + 1e-5f), rs1 = 1.0f / sqrtf(v1 * (1.0f / DM) + 1e-5f);
    uint32_t* o32 = reinterpret_cast<uint32_t*>(g_xn + (size_t)r0 * DM);
#pragma unroll
    for (int j = 0; j < 9; j++) {
      o32[lane + 32 * j] = pack_bf16((bf_lo(xv[0][j]) - m0) * rs0, (bf_hi(xv[0][j]) - m0) * rs0);
      o32[288 + lane + 32 * j] = pack_bf16((bf_lo(xv[1][j]) - m1) * rs1, (bf_hi(xv[1][j]) - m1) * rs1);
    }
  }
}

__device__ __forceinline__ void mod_tail(const bf16* __restrict__ c, const CUtensorMap* tm_wmod, int part, uint8_t* smem, uint32_t bar) {
  const int t = threadIdx.x;
  const uint32_t sb = s2u(smem);
  float* sc = reinterpret_cast<float*>(smem + 2 * 73728);
  float* red = sc + 576;
  auto fill = [&](int b) {
    mbar_expect(bar + 8 * (b & 1), 73728);
    for (int j = 0; j < 3; j++) tma2d(sb + (b & 1) * 73728 + j * 24576, tm_wmod, 1152 + part * 576 + j * 192, b * 64, bar + 8 * (b & 1));
  };
  if (t == 0) { fill(0); fill(1); }
  for (int k = t; k < DM; k += 512) sc[k] = silu_ref(__bfloat162float(c[k]));
  __syncthreads();
  const int cg = t % 72, rg = t / 72;
  float acc[8];
#pragma unroll
  for (int i = 0; i < 8; i++) acc[i] = 0.f;
#pragma unroll 1
  for (int b = 0; b < 9; b++) {
    mbar_wait(bar + 8 * (b & 1), (b >> 1) & 1);
    if (rg < 7) {
#pragma unroll 5
      for (int r = rg; r < 64; r += 7) {
        const uint4 v = lds128(sb + (b & 1) * 73728 + (cg / 24) * 24576 + r * 384 + (cg % 24) * 16);
        const float s = sc[b * 64 + r];
        acc[0] = fmaf(s, bf_lo(v.x), acc[0]); acc[1] = fmaf(s, bf_hi(v.x), acc[1]); acc[2] = fmaf(s, bf_lo(v.y), acc[2]); acc[3] = fmaf(s, bf_hi(v.y), acc[3]);
        acc[4] = fmaf(s, bf_lo(v.z), acc[4]); acc[5] = fmaf(s, bf_hi(v.z), acc[5]); acc[6] = fmaf(s, bf_lo(v.w), acc[6]); acc[7] = fmaf(s, bf_hi(v.w), acc[7]);
      }
    }
    __syncthreads();
    if (t == 0 && b + 2 < 9) fill(b + 2);
  }
  if (rg < 7) {
#pragma unroll
    for (int i = 0; i < 8; i++) red[rg * 576 + cg * 8 + i] = acc[i];
  }
  __syncthreads();
  for (int col = t; col < 576; col += 512) {
    float s = 0.f;
#pragma unroll
    for (int r = 0; r < 7; r++) s += red[r * 576 + col];
    g_mod[1152 + part * 576 + col] = __float2bfloat16_rn(s);
  }
}

constexpr int K1_NST = 5;
constexpr int K1_A = 0, K1_W = 147456, K1_MOD = K1_W + K1_NST * 16384, K1_RED = K1_MOD + 2304, K1_BAR = K1_RED + 256;
constexpr int K1_SMEM = K1_BAR + 8 * (10 + 2 * K1_NST);
#define QSCALE (0.23570226039551584f * 1.4426950408889634f)
#define POLY_MASK 0xFC
__host__ __device__ constexpr bool poly_block(int b) {
  return (POLY_MASK >> b) & 1;
}
constexpr uint32_t KPAD_POLY = 0x42FE47C0u;
constexpr uint32_t VPAD_ONE  = 0x00003F80u;

template <int ST>
__device__ __forceinline__ void k1_load_a(uint32_t (&A)[2][4], const uint32_t (&aoff)[4], uint32_t mtab) {
#pragma unroll
  for (int j = 0; j < 2; j++) {
    ldsm4(A[j], aoff[(ST & 1) * 2 + j] + (ST >> 1) * 16384);
    const uint4 m = lds128(mtab + (ST * 2 + j) * 64);
    A[j][0] = hfma2(A[j][0], m.x, m.z); A[j][1] = hfma2(A[j][1], m.x, m.z);
    A[j][2] = hfma2(A[j][2], m.y, m.w); A[j][3] = hfma2(A[j][3], m.y, m.w);
  }
}
template <int ST>
__device__ __forceinline__ void k1_steps(float (&acc)[108], uint32_t (&A)[3][2][4], const uint32_t (&aoff)[4], uint32_t mtab, uint64_t db0,
                                         uint32_t bx, uint32_t bwf, uint32_t rbe, bool releaser) {
  if constexpr (ST < 18) {
    constexpr int s = ST % K1_NST;
    mbar_wait(bwf + 8 * s, (ST / K1_NST) & 1);
    fence_regs(A[ST % 3][0]); fence_regs(A[ST % 3][1]);
    wg_fence();
#pragma unroll
    for (int j = 0; j < 2; j++)
      wgmma_rs_n216_tb(acc, A[ST % 3][j][0], A[ST % 3][j][1], A[ST % 3][j][2], A[ST % 3][j][3], db0 + (uint64_t)(s * 1024 + j * 128), 1);
    wg_commit();
    if constexpr (ST + 1 < 18) {
      if constexpr (((ST + 1) & 1) == 0) mbar_wait(bx + 8 * ((ST + 1) >> 1), 0);
      k1_load_a<ST + 1>(A[(ST + 1) % 3], aoff, mtab);
    }
    if constexpr (ST > 0) {
      wg_wait<1>();
      if (ST - 1 + K1_NST < 18 && releaser) mbar_arrive_remote(rbe + 8 * ((ST - 1) % K1_NST));
    }
    k1_steps<ST + 1>(acc, A, aoff, mtab, db0, bx, bwf, rbe, releaser);
  }
}

__host__ __device__ constexpr int k1_off(int I, int Q) {
  const int col = 8 * I + 2 * Q, sl = col / 18, d = col % 18;
  return sl * 6144 + (d >> 3) * 128 + (d & 7) * 2 - 4 * Q;
}
template <int I>
__device__ __forceinline__ void k1_stage_block(const float (&acc)[108], uint32_t base, int q4, int nq) {
  uint32_t a = base + k1_off(I, 0);
  if constexpr (k1_off(I, 1) != k1_off(I, 0)) a += q4 >= 1 ? k1_off(I, 1) - k1_off(I, 0) : 0;
  if constexpr (k1_off(I, 2) != k1_off(I, 1)) a += q4 >= 2 ? k1_off(I, 2) - k1_off(I, 1) : 0;
  if constexpr (k1_off(I, 3) != k1_off(I, 2)) a += q4 >= 3 ? k1_off(I, 3) - k1_off(I, 2) : 0;
  constexpr int s0 = (8 * I) / 18, s3 = (8 * I + 6) / 18, qs = s0 == s3 ? 4 : (18 * s3 - 8 * I) / 2;
  const float sc = ((q4 >= qs ? s3 : s0) < nq) ? QSCALE : 1.0f;
  sts32(a, pack_bf16(acc[4 * I] * sc, acc[4 * I + 1] * sc));
  sts32(a + 384, pack_bf16(acc[4 * I + 2] * sc, acc[4 * I + 3] * sc));
}
template <int G>
__device__ __forceinline__ void k1_stage_group(const float (&acc)[108], uint32_t base, uint32_t pbase, uint32_t kpad, int q4, int nt, int rb, int tid,
                                               uint32_t sb) {
  const int nq = 32 - 12 * nt;
  k1_stage_block<9 * G + 0>(acc, base, q4, nq); k1_stage_block<9 * G + 1>(acc, base, q4, nq); k1_stage_block<9 * G + 2>(acc, base, q4, nq);
  k1_stage_block<9 * G + 3>(acc, base, q4, nq); k1_stage_block<9 * G + 4>(acc, base, q4, nq); k1_stage_block<9 * G + 5>(acc, base, q4, nq);
  k1_stage_block<9 * G + 6>(acc, base, q4, nq); k1_stage_block<9 * G + 7>(acc, base, q4, nq); k1_stage_block<9 * G + 8>(acc, base, q4, nq);
#pragma unroll
  for (int i = 0; i < 2; i++) {
    const int slot = nt * 12 + 4 * G + 2 * i + (tid >> 7);
    const uint32_t pad = slot >= 64 ? VPAD_ONE : (slot >= 32 ? kpad : 0u);
    const uint32_t a = pbase + (4 * G + 2 * i) * 6144;
    sts32(a + 4, pad);
    asm volatile("st.shared.v2.b32 [%0], {%1, %1};" :: "r"(a + 8), "r"(0u) : "memory");
  }
  fence_async_smem();
  bar_sync(1, 256);
  if (tid == 0) {
#pragma unroll
    for (int sl = 4 * G; sl < 4 * G + 4; sl++)
      bulk_s2g(g_qkvp + (size_t)(nt * 12 + sl) * SLOT_BYTES + (size_t)rb * 6144, sb + sl * 6144, 6144);
    bulk_commit();
  }
}

__device__ __forceinline__ void transpose_wo_block(const bf16* __restrict__ wo, int kb, int nb, int lane) {
  const int h = lane & 1;
  uint4 v[2][8];
#pragma unroll
  for (int u = 0; u < 2; u++)
#pragma unroll
    for (int g = 0; g < 8; g++) v[u][g] = __ldg(reinterpret_cast<const uint4*>(wo + (size_t)(kb * 64 + u * 32 + lane) * DM + nb * 64 + g * 8));
  uint32_t* dst = reinterpret_cast<uint32_t*>(g_woT) + (size_t)(nb * 64 + 4 * h) * (DM / 2) + kb * 32 + (lane >> 1);
#pragma unroll
  for (int u = 0; u < 2; u++)
#pragma unroll
    for (int g = 0; g < 8; g++) {
      const uint32_t r0 = __shfl_xor_sync(0xffffffffu, h ? v[u][g].x : v[u][g].z, 1), r1 = __shfl_xor_sync(0xffffffffu, h ? v[u][g].y : v[u][g].w, 1);
      const uint32_t o0 = h ? v[u][g].z : v[u][g].x, o1 = h ? v[u][g].w : v[u][g].y;
      const uint32_t l0 = h ? r0 : o0, l1 = h ? r1 : o1, h0 = h ? o0 : r0, h1 = h ? o1 : r1;
      uint32_t* d = dst + (size_t)g * 8 * (DM / 2) + u * 16;
      d[0 * (DM / 2)] = __byte_perm(l0, h0, 0x5410); d[1 * (DM / 2)] = __byte_perm(l0, h0, 0x7632);
      d[2 * (DM / 2)] = __byte_perm(l1, h1, 0x5410); d[3 * (DM / 2)] = __byte_perm(l1, h1, 0x7632);
    }
}

__global__ void __launch_bounds__(352, 1) k1_qkv(const __grid_constant__ CUtensorMap tm_xn, const __grid_constant__ CUtensorMap tm_w, const bf16* __restrict__ wo) {
  extern __shared__ __align__(1024) uint8_t smem[];
  const uint32_t sb = s2u(smem);
  const int tid = threadIdx.x, nt = (blockIdx.x >> 1) & 7, rb = (blockIdx.x >> 4) * 2 + (blockIdx.x & 1);
  const uint32_t bx = sb + K1_BAR, bmp = bx + 72, bwf = bmp + 8, bwe = bwf + 8 * K1_NST;
  TL(1, 0);
  if (tid == 256) {
    for (int i = 0; i < 10; i++) mbar_init(bx + 8 * i, 1);
    for (int i = 0; i < K1_NST; i++) { mbar_init(bwf + 8 * i, 1); mbar_init(bwe + 8 * i, 4); }
    fence_barrier_init();
    tmap_prefetch(&tm_xn); tmap_prefetch(&tm_w);
  }
  __syncthreads();
  cluster_arrive_relaxed();
  pdl_launch();
  if (tid >= 320) {
    if (blockIdx.x < 81) transpose_wo_block(wo, blockIdx.x / 9, blockIdx.x % 9, tid & 31);
    cluster_wait();
    return;
  }
  if (tid >= 288) {
    if (tid == 288) {
      auto load_x = [&](int c) { mbar_expect(bx + 8 * c, 16384); tma2d(sb + K1_A + c * 16384, &tm_xn, c * 64, rb * 128, bx + 8 * c); };
      pdl_wait();
      mbar_expect(bmp, MODP * 2 * DM * 4); bulk_g2s(sb + K1_A + 8 * 16384, g_modp, MODP * 2 * DM * 4, bmp);
      load_x(0); load_x(1); load_x(2);
      for (int c = 3; c < 9; c++) { mbar_wait(bx + 8 * (c - 3), 0); if (c == 8) mbar_wait(bwe, 0); load_x(c); }
    }
    __syncwarp();
    cluster_wait();
    return;
  }
  if (tid >= 256) {
    cluster_wait();
    if (tid == 256) {
      const int rank = cluster_rank();
      auto load_w = [&](int st) {
        const int s = st % K1_NST;
        mbar_expect(bwf + 8 * s, 16384);
        for (int g = 2 * rank; g < 2 * rank + 2; g++) tma2d_mc(sb + K1_W + s * 16384 + g * 4096, &tm_w, nt * 216 + g * 64, st * 32, bwf + 8 * s);
      };
      for (int st = 0; st < K1_NST; st++) load_w(st);
      if (rb < 8) for (int b = rb; b < (18 - K1_NST) * 4; b += 8) tma2d_prefetch(&tm_w, nt * 216 + (b & 3) * 64, (K1_NST + (b >> 2)) * 32);
      for (int st = K1_NST; st < 18; st++) {
        mbar_wait(bwe + 8 * (st % K1_NST), (st / K1_NST - 1) & 1);
        load_w(st);
      }
    }
    __syncwarp();
    cluster_arrive_relaxed(); cluster_wait();
    return;
  }
  cluster_wait();
  const int wg = __reduce_max_sync(0xffffffffu, (unsigned)tid >> 7), wtid = tid & 127, warp = (tid >> 5) & 3, lane = tid & 31, g = lane >> 2, q4 = lane & 3;
  const uint32_t rbe = map_cta(bwe, wtid & 1);
  TL(1, 1);
  {
    const float2* mp = reinterpret_cast<const float2*>(smem + K1_A + 8 * 16384);
    mbar_wait(bmp, 0);
    for (int i = tid; i < 288; i += 256) {
      float2 s0 = mp[i], c0 = mp[288 + i];
#pragma unroll
      for (int p = 1; p < MODP; p++) {
        const float2 s1 = mp[p * 576 + i], c1 = mp[p * 576 + 288 + i];
        s0.x += s1.x; s0.y += s1.y; c0.x += c1.x; c0.y += c1.y;
      }
      const uint32_t a = sb + K1_MOD + (i >> 3) * 64 + (i & 3) * 16 + ((i >> 2) & 1) * 4;
      sts32(a, hadd2(pack_bf16(c0.x, c0.y), 0x3F803F80u));
      sts32(a + 8, pack_bf16(s0.x, s0.y));
    }
  }
  bar_sync(1, 256);
  TL(1, 4);
  uint32_t aoff[4];
  {
    const int r = wg * 64 + warp * 16 + (lane & 7) + ((lane >> 3) & 1) * 8;
#pragma unroll
    for (int j = 0; j < 4; j++) aoff[j] = opaque(sb + K1_A + r * 128 + (((2 * j + (lane >> 4)) ^ (lane & 7)) << 4));
  }
  const uint32_t mtab = opaque(sb + K1_MOD + q4 * 16);
  float acc[108];
#pragma unroll
  for (int i = 0; i < 108; i++) acc[i] = 0.f;
  const uint64_t db0 = mkdesc(sb + K1_W, 4096, 1024, 1);
  uint32_t A[3][2][4];
  mbar_wait(bx, 0);
  TL(1, 5);
  k1_load_a<0>(A[0], aoff, mtab);
  k1_steps<0>(acc, A, aoff, mtab, db0, bx, bwf, rbe, wtid < 2);
  wg_wait<0>();
  fence_regs(acc);
  cluster_arrive_relaxed();
  TL(1, 2);
  bar_sync(1, 256);
  {
    const int tok = wg * 64 + warp * 16 + g;
    const uint32_t base = opaque(sb + (tok >> 3) * 384 + (tok & 7) * 16 + q4 * 4);
    const int tk = tid & 127;
    const uint32_t pbase = opaque(sb + (tid >> 7) * 6144 + (tk >> 3) * 384 + (tk & 7) * 16 + 256);
    const uint32_t kpad = poly_block((tk >> 3) & 7) ? KPAD_POLY : 0u;
    k1_stage_group<0>(acc, base, pbase, kpad, q4, nt, rb, tid, sb);
    k1_stage_group<1>(acc, base, pbase, kpad, q4, nt, rb, tid, sb);
    k1_stage_group<2>(acc, base, pbase, kpad, q4, nt, rb, tid, sb);
  }
  TL(1, 3);
  if (nt * 12 < 64) {
    const int tok = tid & 127;
    float* red = reinterpret_cast<float*>(smem + K1_RED);
#pragma unroll
    for (int i = 0; i < 6; i++) {
      const int sl = (tid >> 7) + 2 * i;
      const uint32_t a = sb + sl * 6144 + (tok >> 3) * 384 + (tok & 7) * 16;
      const uint4 v0 = lds128(a), v1 = lds128(a + 128);
      const uint32_t v2 = lds32(a + 256);
      float n2 = 0.f;
      const uint32_t w[9] = {v0.x, v0.y, v0.z, v0.w, v1.x, v1.y, v1.z, v1.w, v2};
#pragma unroll
      for (int j = 0; j < 9; j++) { n2 = fmaf(bf_lo(w[j]), bf_lo(w[j]), n2); n2 = fmaf(bf_hi(w[j]), bf_hi(w[j]), n2); }
      const uint32_t mx = __reduce_max_sync(0xffffffffu, __float_as_uint(n2) & 0x7FFFFFFFu);
      if (lane == 0) red[sl * 4 + warp] = __uint_as_float(mx);
    }
    bar_sync(1, 256);
    if (tid >= 32 && tid < 44) {
      const int sl = tid - 32, slot = nt * 12 + sl;
      const uint32_t* r = reinterpret_cast<const uint32_t*>(red) + sl * 4;
      if (slot < 64) g_nrm[slot * 16 + rb] = __uint_as_float(max(max(r[0], r[1]), max(r[2], r[3])));
    }
  }
  if (tid == 0) bulk_wait_read();
  TL(1, 7);
  cluster_wait();
}

constexpr int K2_K = 0, K2_V = SLOT_BYTES, K2_Q = 2 * SLOT_BYTES, K2_BAR = K2_Q + 512 * 48, K2_SMEM = K2_BAR + 8 * 19;
constexpr uint32_t EXP_C2 = 0x3EA93EA9u, EXP_C1 = 0x3B4E3B4Eu, EXP_C0 = 0x3F2C3F2Cu;
constexpr int K2_TD = 8 * 384 / 16;

__device__ __forceinline__ void attn_qk(float (&S)[32], const uint32_t (&q)[8], uint64_t kd) {
  wgmma_rs0_n64(S, q[0], q[1], q[2], q[3], kd);
  wgmma_rs_n64(S, q[4], q[5], q[6], q[7], kd + 16, 1);
}
__device__ __forceinline__ void attn_pv(float (&O)[12], const uint32_t (&P)[16], uint64_t vd) {
#pragma unroll
  for (int kk = 0; kk < 4; kk++) wgmma_rs_n24_tb(O, P[4 * kk], P[4 * kk + 1], P[4 * kk + 2], P[4 * kk + 3], vd + kk * 48, 1);
}
__device__ __forceinline__ void attn_exp(float (&S)[32], uint32_t c2, uint32_t cone) {
#pragma unroll
  for (int b = 0; b < 8; b++) {
    if (poly_block(b)) {
#pragma unroll
      for (int h = 0; h < 2; h++) {
        uint32_t w, y;
        asm("prmt.b32 %0, %1, %2, 0x5410;" : "=r"(w) : "r"(__float_as_uint(S[4 * b + 2 * h])), "r"(__float_as_uint(S[4 * b + 2 * h + 1])));
        asm("lop3.b32 %0, %1, 0x007F007F, %2, 0xEA;" : "=r"(y) : "r"(w), "r"(cone));
        const uint32_t p = hfma2(hfma2(y, c2, EXP_C1), y, EXP_C0);
        S[4 * b + 2 * h] = __uint_as_float(w);
        S[4 * b + 2 * h + 1] = __uint_as_float(p);
      }
    } else {
#pragma unroll
      for (int j = 0; j < 4; j++) S[4 * b + j] = ex2(S[4 * b + j]);
    }
  }
}
__device__ __forceinline__ void attn_pack(const float (&S)[32], uint32_t (&P)[16]) {
#pragma unroll
  for (int i = 0; i < 16; i++) {
    if (poly_block(i >> 1)) asm("lop3.b32 %0, %1, %2, 0xFF80FF80, 0xE4;" : "=r"(P[i]) : "r"(__float_as_uint(S[2 * i])), "r"(__float_as_uint(S[2 * i + 1])));
    else P[i] = pack_bf16(S[2 * i], S[2 * i + 1]);
  }
}

__device__ __forceinline__ void attn_load_chunk(uint32_t sb, uint32_t bar, const uint8_t* Kg, int c) {
  mbar_expect(bar + 8 * c, 2 * 6144);
  bulk_g2s(sb + K2_K + c * 6144, Kg + c * 6144, 6144, bar + 8 * c);
  bulk_g2s(sb + K2_V + c * 6144, Kg + (size_t)32 * SLOT_BYTES + c * 6144, 6144, bar + 8 * c);
}

template <bool WAIT>
__device__ __forceinline__ void attn_fast_pass(float (&O)[12], const uint32_t (&q)[8], uint64_t kd, uint64_t vd, uint32_t bar) {
  float S[32]; uint32_t P[16];
  const uint32_t c2 = opaque(EXP_C2), cone = opaque(0x3F803F80u);
  if (WAIT) mbar_wait(bar, 0);
  wg_fence();
  attn_qk(S, q, kd);
  wg_commit();
  wg_wait<0>();
  fence_regs(S);
  attn_exp(S, c2, cone);
  attn_pack(S, P);
  auto step = [&]() {
    kd += K2_TD;
    fence_regs(P); fence_regs(O);
    wg_fence();
    attn_qk(S, q, kd);
    wg_commit();
    attn_pv(O, P, vd);
    wg_commit();
    vd += K2_TD;
    wg_wait<1>();
    fence_regs(S);
    attn_exp(S, c2, cone);
    fence_regs(S);
    wg_wait<0>();
    fence_regs(S); fence_regs(O);
    attn_pack(S, P);
  };
#pragma unroll 1
  for (int c = 1; c < 16; c++) {
    step();
    if (WAIT) mbar_wait(bar + 8 * c, 0);
    step();
  }
  step();
  fence_regs(P); fence_regs(O);
  wg_fence();
  attn_pv(O, P, vd);
  wg_commit();
  wg_wait<0>();
  fence_regs(O);
}

__device__ __forceinline__ void attn_safe_pass(float (&O)[12], const uint32_t (&q)[8], uint64_t kd, uint64_t vd, uint32_t bar) {
  float S[32]; uint32_t P[16];
  float m0 = -INFINITY, m1 = -INFINITY;
#pragma unroll 1
  for (int j = 0; j < 32; j++) {
    if ((j & 1) == 0) mbar_wait(bar + 8 * (j >> 1), 0);
    wg_fence();
    attn_qk(S, q, kd);
    wg_commit();
    wg_wait<0>();
    fence_regs(S);
    float x0 = m0, x1 = m1;
#pragma unroll
    for (int b = 0; b < 8; b++) { x0 = fmaxf(x0, fmaxf(S[4 * b], S[4 * b + 1])); x1 = fmaxf(x1, fmaxf(S[4 * b + 2], S[4 * b + 3])); }
    x0 = fmaxf(x0, __shfl_xor_sync(0xffffffffu, x0, 1)); x0 = fmaxf(x0, __shfl_xor_sync(0xffffffffu, x0, 2));
    x1 = fmaxf(x1, __shfl_xor_sync(0xffffffffu, x1, 1)); x1 = fmaxf(x1, __shfl_xor_sync(0xffffffffu, x1, 2));
    const float a0 = ex2(m0 - x0), a1 = ex2(m1 - x1);
    m0 = x0; m1 = x1;
#pragma unroll
    for (int b = 0; b < 3; b++) { O[4 * b] *= a0; O[4 * b + 1] *= a0; O[4 * b + 2] *= a1; O[4 * b + 3] *= a1; }
#pragma unroll
    for (int b = 0; b < 8; b++) {
      P[2 * b] = pack_bf16(ex2(S[4 * b] - m0), ex2(S[4 * b + 1] - m0));
      P[2 * b + 1] = pack_bf16(ex2(S[4 * b + 2] - m1), ex2(S[4 * b + 3] - m1));
    }
    fence_regs(P); fence_regs(O);
    wg_fence();
    attn_pv(O, P, vd);
    wg_commit();
    wg_wait<0>();
    fence_regs(O);
    kd += K2_TD; vd += K2_TD;
  }
}

__global__ void __launch_bounds__(512, 1) k2_attn(const __grid_constant__ CUtensorMap tm_wmod, const bf16* __restrict__ cvec,
                                                   const bf16* __restrict__ w1, const bf16* __restrict__ w2) {
  extern __shared__ __align__(1024) uint8_t smem[];
  const uint32_t sb = s2u(smem);
  const int head = blockIdx.x >> 2, qg = blockIdx.x & 3;
  const int tid = threadIdx.x, wg = __reduce_max_sync(0xffffffffu, (unsigned)tid >> 7), warp = (tid >> 5) & 3, lane = tid & 31, g = lane >> 2, q4 = lane & 3;
  const uint32_t bar = sb + K2_BAR;
  TL(2, 0);
  if (tid == 0) {
    for (int i = 0; i < 18; i++) mbar_init(bar + 8 * i, 1);
    fence_barrier_init();
  }
  __syncthreads();
  if (blockIdx.x >= 128) {
    mod_tail(cvec, &tm_wmod, blockIdx.x - 128, smem, bar);
    pdl_wait();
    return;
  }
  pdl_wait();
  pdl_launch();
  TL(2, 3);
  if ((tid >> 5) == 1) {
    uint32_t nv = 0;
    if (lane < 16) nv = __float_as_uint(__ldcg(&g_nrm[(32 + head) * 16 + lane]));
    else if (lane < 20) nv = __float_as_uint(__ldcg(&g_nrm[head * 16 + qg * 4 + lane - 16]));
    const uint32_t km = __reduce_max_sync(0xffffffffu, lane < 16 ? nv : 0u), qm = __reduce_max_sync(0xffffffffu, lane < 16 ? 0u : nv);
    if (lane == 0) sts32(bar + 8 * 18, __uint_as_float(km) * __uint_as_float(qm) <= 4096.0f ? 1u : 0u);
  }
  const uint8_t* Kg = g_qkvp + (size_t)(32 + head) * SLOT_BYTES;
  bool fast;
  {
    const uint8_t* Qg = g_qkvp + (size_t)head * SLOT_BYTES + (size_t)qg * 512 * 48;
    if (tid == 0) {
      mbar_expect(bar + 8 * 16, 4 * 3072);
      for (int w = 0; w < 4; w++) bulk_g2s(sb + K2_Q + w * 6144, Qg + w * 6144, 3072, bar + 8 * 16);
      for (int c = 0; c < 2; c++) attn_load_chunk(sb, bar, Kg, c);
    }
    __syncthreads();
    fast = lds32(bar + 8 * 18) != 0;
    if (tid == 32) {
      for (int c = 2; c < 16; c++) attn_load_chunk(sb, bar, Kg, c);
      mbar_expect(bar + 8 * 17, 4 * 3072);
      for (int w = 0; w < 4; w++) bulk_g2s(sb + K2_Q + w * 6144 + 3072, Qg + w * 6144 + 3072, 3072, bar + 8 * 17);
    }
    __syncwarp();
  }
  TL(2, 1);
  const uint64_t kd = mkdesc(sb + K2_K, 128, 384, 0);
  const uint64_t vd = mkdesc(sb + K2_V, 384, 128, 0);
#pragma unroll 1
  for (int it = 0; it < 2; it++) {
    const int qt = wg * 2 + it;
    mbar_wait(bar + 8 * (16 + it), 0);
    if (it == 0) TL(2, 4);
    uint32_t q[8];
    {
      const uint32_t base = sb + K2_Q + (qt * 8 + warp * 2) * 384 + g * 16 + q4 * 4;
#pragma unroll
      for (int j = 0; j < 3; j++) { q[2 * j] = lds32(base + j * 128); q[2 * j + 1] = lds32(base + 384 + j * 128); }
      if (fast && q4 == 1) { q[4] = 0x3F803F80u; q[5] = 0x3F803F80u; }
      q[6] = opaque(0u); q[7] = opaque(0u);
    }
    if (it == 1 && tid == 0) {
      const char* a = reinterpret_cast<const char*>(w1) + (size_t)blockIdx.x * (DM * FF * 2 / 128);
      const char* b = reinterpret_cast<const char*>(w2) + (size_t)blockIdx.x * (DM * FF * 2 / 128);
      asm volatile("cp.async.bulk.prefetch.L2.global [%0], %1;" :: "l"(a), "r"(DM * FF * 2 / 128) : "memory");
      asm volatile("cp.async.bulk.prefetch.L2.global [%0], %1;" :: "l"(b), "r"(DM * FF * 2 / 128) : "memory");
    }
    float O[12];
#pragma unroll
    for (int i = 0; i < 12; i++) O[i] = 0.f;
    if (fast) {
      if (it == 0) attn_fast_pass<true>(O, q, kd, vd, bar);
      else attn_fast_pass<false>(O, q, kd, vd, bar);
    } else {
      attn_safe_pass(O, q, kd, vd, bar);
    }
    const float l0 = __shfl_sync(0xffffffffu, O[8], (lane & ~3) | 1), l1 = __shfl_sync(0xffffffffu, O[10], (lane & ~3) | 1);
    const float r0 = __frcp_rn(l0), r1 = __frcp_rn(l1);
    const int row = qg * 512 + qt * 64 + warp * 16 + g;
    uint32_t* o0 = reinterpret_cast<uint32_t*>(g_o + (size_t)row * DM + head * DHEAD + q4 * 2);
    uint32_t* o1 = o0 + 8 * DM / 2;
    o0[0] = pack_bf16(O[0] * r0, O[1] * r0);  o1[0] = pack_bf16(O[2] * r1, O[3] * r1);
    o0[4] = pack_bf16(O[4] * r0, O[5] * r0);  o1[4] = pack_bf16(O[6] * r1, O[7] * r1);
    if (q4 == 0) { o0[8] = pack_bf16(O[8] * r0, O[9] * r0);  o1[8] = pack_bf16(O[10] * r1, O[11] * r1); }
  }
  TL(2, 7);
}

constexpr int K3_A = 0, K3_W = 147456, K3_X = K3_W, K3_MOD = K3_W + 9 * 9216, K3_BAR = K3_MOD + 3 * 144 + 16;
constexpr int K3_SMEM = K3_BAR + 8 * (9 + 9 + 3);

__global__ void __launch_bounds__(320, 1) k3_wo(const __grid_constant__ CUtensorMap tm_o, const __grid_constant__ CUtensorMap tm_wo,
                                                const __grid_constant__ CUtensorMap tm_x, const __grid_constant__ CUtensorMap tm_x2,
                                                const __grid_constant__ CUtensorMap tm_h2) {
  extern __shared__ __align__(1024) uint8_t smem[];
  const uint32_t sb = s2u(smem);
  const int tid = threadIdx.x, nt = blockIdx.x & 7, rb = blockIdx.x >> 3;
  const uint32_t bw = sb + K3_BAR, baf = bw + 72, bxb = baf + 72, bmd = bxb + 8, bxe = bmd + 8;
  TL(3, 0);
  if (tid == 256) {
    for (int i = 0; i < 20; i++) mbar_init(bw + 8 * i, 1);
    mbar_init(bxe, 2);
    fence_barrier_init();
    tmap_prefetch(&tm_o); tmap_prefetch(&tm_wo); tmap_prefetch(&tm_x); tmap_prefetch(&tm_x2); tmap_prefetch(&tm_h2);
  }
  __syncthreads();
  cluster_arrive_relaxed();
  pdl_launch();
  if (tid >= 288) {
    if (tid == 288)
      for (int c = 0; c < 9; c++) { mbar_expect(bw + 8 * c, 9216); tma2d(sb + K3_W + c * 9216, &tm_wo, c * 64, nt * 72, bw + 8 * c); }
    __syncwarp();
    cluster_wait();
    return;
  }
  if (tid >= 256) {
    cluster_wait();
    if (tid == 256) {
      const int rank = cluster_rank();
      pdl_wait();
      for (int c = 0; c < 9; c++) {
        mbar_expect(baf + 8 * c, 16384);
        tma2d_mc(sb + K3_A + c * 16384 + rank * 8192, &tm_o, c * 64, rb * 128 + rank * 64, baf + 8 * c);
      }
      mbar_expect(bmd, 3 * 144);
      for (int v = 0; v < 3; v++) bulk_g2s(sb + K3_MOD + v * 144, g_mod + (2 + v) * DM + nt * 72, 144, bmd);
      mbar_wait(bxe, 0);
      mbar_expect(bxb, 18432); tma2d(sb + K3_X, &tm_x, nt * 72, rb * 128, bxb);
    }
    __syncwarp();
    cluster_arrive_relaxed(); cluster_wait();
    return;
  }
  const int wg = __reduce_max_sync(0xffffffffu, (unsigned)tid >> 7), wtid = tid & 127, warp = (tid >> 5) & 3, lane = tid & 31, g = lane >> 2, q4 = lane & 3;
  const int lrow = wg * 64 + warp * 16 + g;
  cluster_wait();
  pdl_wait();
  TL(3, 1);
  const uint32_t tag = __ldcg(&g_epoch);
  float acc[36];
#pragma unroll
  for (int i = 0; i < 36; i++) acc[i] = 0.f;
  const uint64_t da0 = mkdesc(sb + K3_A + wg * 8192, 16, 1024, 1);
  const uint64_t db0 = mkdesc(sb + K3_W, 16, 1024, 1);
#pragma unroll 1
  for (int c = 0; c < 9; c++) {
    mbar_wait(bw + 8 * c, 0);
    mbar_wait(baf + 8 * c, 0);
    wg_fence();
#pragma unroll
    for (int j = 0; j < 4; j++) wgmma_ss_n72(acc, da0 + (uint64_t)(c * 1024 + j * 2), db0 + (uint64_t)(c * 576 + j * 2), 1);
    wg_commit();
    if (c == 2) { wg_wait<1>(); if (wtid == 0) mbar_arrive(bxe); }
  }
  wg_wait<0>();
  fence_regs(acc);
  cluster_arrive_relaxed();
  TL(3, 2);
  mbar_wait(bmd, 0);
  mbar_wait(bxb, 0);
  const uint32_t xa = sb + K3_X + lrow * 144 + q4 * 4, ma = sb + K3_MOD + q4 * 4;
  float s0 = 0.f, s1 = 0.f;
#pragma unroll
  for (int i = 0; i < 9; i++) {
    const uint32_t x0 = lds32(xa + 16 * i), x1 = lds32(xa + 8 * 144 + 16 * i), ga = lds32(ma + 16 * i);
    const float g0 = bf_lo(ga), g1 = bf_hi(ga);
    const uint32_t p0 = pack_bf16(fmaf(g0, acc[4 * i], bf_lo(x0)), fmaf(g1, acc[4 * i + 1], bf_hi(x0)));
    const uint32_t p1 = pack_bf16(fmaf(g0, acc[4 * i + 2], bf_lo(x1)), fmaf(g1, acc[4 * i + 3], bf_hi(x1)));
    sts32(xa + 16 * i, p0); sts32(xa + 8 * 144 + 16 * i, p1);
    acc[4 * i] = bf_lo(p0); acc[4 * i + 1] = bf_hi(p0); acc[4 * i + 2] = bf_lo(p1); acc[4 * i + 3] = bf_hi(p1);
    s0 += acc[4 * i] + acc[4 * i + 1]; s1 += acc[4 * i + 2] + acc[4 * i + 3];
  }
  s0 += __shfl_xor_sync(0xffffffffu, s0, 1); s1 += __shfl_xor_sync(0xffffffffu, s1, 1);
  s0 += __shfl_xor_sync(0xffffffffu, s0, 2); s1 += __shfl_xor_sync(0xffffffffu, s1, 2);
  const float m0 = s0 * (1.0f / 72), m1 = s1 * (1.0f / 72);
  float v0 = 0.f, v1 = 0.f;
#pragma unroll
  for (int i = 0; i < 9; i++) {
    float d;
    d = acc[4 * i] - m0; v0 = fmaf(d, d, v0); d = acc[4 * i + 1] - m0; v0 = fmaf(d, d, v0);
    d = acc[4 * i + 2] - m1; v1 = fmaf(d, d, v1); d = acc[4 * i + 3] - m1; v1 = fmaf(d, d, v1);
  }
  v0 += __shfl_xor_sync(0xffffffffu, v0, 1); v1 += __shfl_xor_sync(0xffffffffu, v1, 1);
  v0 += __shfl_xor_sync(0xffffffffu, v0, 2); v1 += __shfl_xor_sync(0xffffffffu, v1, 2);
  if (q4 < 2) {
    const float mm = q4 ? m1 : m0, vv = q4 ? v1 : v0;
    asm volatile("st.relaxed.gpu.global.v2.b64 [%0], {%1, %2};"
                 :: "l"(&g_stats[(rb * 8 + nt) * 128 + lrow + 8 * q4]), "l"(((uint64_t)tag << 32) | __float_as_uint(mm)), "l"(((uint64_t)tag << 32) | __float_as_uint(vv)) : "memory");
  }
  fence_async_smem();
  bar_sync(1, 256);
  TL(3, 3);
  if (tid == 0) { tma2d_store(&tm_x2, sb + K3_X, nt * 72, rb * 128); bulk_commit(); }
  float mean0, mean1, rs0, rs1;
  {
    uint64_t w[8];
    const uint4* pa = &g_stats[(rb * 8 + 2 * q4) * 128 + lrow];
    for (int it = 0; it < (1 << 20); it++) {
      asm volatile("ld.relaxed.gpu.global.v2.b64 {%0, %1}, [%2];" : "=l"(w[0]), "=l"(w[1]) : "l"(pa) : "memory");
      asm volatile("ld.relaxed.gpu.global.v2.b64 {%0, %1}, [%2];" : "=l"(w[2]), "=l"(w[3]) : "l"(pa + 128) : "memory");
      asm volatile("ld.relaxed.gpu.global.v2.b64 {%0, %1}, [%2];" : "=l"(w[4]), "=l"(w[5]) : "l"(pa + 8) : "memory");
      asm volatile("ld.relaxed.gpu.global.v2.b64 {%0, %1}, [%2];" : "=l"(w[6]), "=l"(w[7]) : "l"(pa + 136) : "memory");
      bool ok = true;
#pragma unroll
      for (int j = 0; j < 8; j++) ok = ok && (uint32_t)(w[j] >> 32) == tag;
      if (__all_sync(0xffffffffu, ok)) break;
      __nanosleep(200);
    }
    const float ax = __uint_as_float((uint32_t)w[0]), ay = __uint_as_float((uint32_t)w[1]), az = __uint_as_float((uint32_t)w[2]), aw = __uint_as_float((uint32_t)w[3]);
    const float bx = __uint_as_float((uint32_t)w[4]), by = __uint_as_float((uint32_t)w[5]), bz = __uint_as_float((uint32_t)w[6]), bw_ = __uint_as_float((uint32_t)w[7]);
    float sa = ax + az, sb_ = bx + bz;
    sa += __shfl_xor_sync(0xffffffffu, sa, 1); sb_ += __shfl_xor_sync(0xffffffffu, sb_, 1);
    sa += __shfl_xor_sync(0xffffffffu, sa, 2); sb_ += __shfl_xor_sync(0xffffffffu, sb_, 2);
    mean0 = sa * 0.125f; mean1 = sb_ * 0.125f;
    float ma2 = ay + aw + 72.f * ((ax - mean0) * (ax - mean0) + (az - mean0) * (az - mean0));
    float mb2 = by + bw_ + 72.f * ((bx - mean1) * (bx - mean1) + (bz - mean1) * (bz - mean1));
    ma2 += __shfl_xor_sync(0xffffffffu, ma2, 1); mb2 += __shfl_xor_sync(0xffffffffu, mb2, 1);
    ma2 += __shfl_xor_sync(0xffffffffu, ma2, 2); mb2 += __shfl_xor_sync(0xffffffffu, mb2, 2);
    rs0 = rsqrtf(ma2 * (1.0f / DM) + 1e-5f); rs1 = rsqrtf(mb2 * (1.0f / DM) + 1e-5f);
  }
  TL(3, 4);
  {
    const uint32_t ha = sb + K3_A + lrow * 144 + q4 * 4;
#pragma unroll
    for (int i = 0; i < 9; i++) {
      const uint32_t c1p = hadd2(lds32(ma + 288 + 16 * i), 0x3F803F80u), sh = lds32(ma + 144 + 16 * i);
      sts32(ha + 16 * i, hfma2(hfma2(pack_bf16((acc[4 * i] - mean0) * rs0, (acc[4 * i + 1] - mean0) * rs0), c1p, sh), 0x3F003F00u, 0x80008000u));
      sts32(ha + 8 * 144 + 16 * i, hfma2(hfma2(pack_bf16((acc[4 * i + 2] - mean1) * rs1, (acc[4 * i + 3] - mean1) * rs1), c1p, sh), 0x3F003F00u, 0x80008000u));
    }
  }
  fence_async_smem();
  bar_sync(1, 256);
  if (tid == 0) { tma2d_store(&tm_h2, sb + K3_A, nt * 72, rb * 128); bulk_commit(); bulk_wait_read(); }
  TL(3, 7);
  cluster_wait();
}

constexpr int K4_BK = 64;
constexpr int K4_KS = K4_BK / 16;
constexpr int K4_SPT = 576 / K4_BK;
constexpr int K4_NST = 3 * 64 / K4_BK;
constexpr int K4_STB = K4_BK * 384;
constexpr int K4_A = 0, K4_B = 147456, K4_BAR = K4_B + K4_NST * K4_STB, K4_SMEM = K4_BAR + 8 * (9 + 2 * K4_NST) + 8;

__device__ __forceinline__ uint32_t silu2(uint32_t v, uint32_t m16, uint32_t mhi) {
  const float lo = __uint_as_float(v * m16), hi = __uint_as_float(v & mhi);
  return pack_bf16(fmaf(lo, tanh_fast(lo), lo), fmaf(hi, tanh_fast(hi), hi));
}
template <int P>
__device__ __forceinline__ void k4_epi(const uint32_t (&pk)[48], uint32_t go, bf16* hp) {
  const uint32_t m16 = go << 16, mhi = 0u - m16;
  constexpr int B = 8 * (P >> 1) + (P & 1);
  uint4 r;
  r.x = silu2(pk[B], m16, mhi); r.y = silu2(pk[B + 2], m16, mhi); r.z = silu2(pk[B + 4], m16, mhi); r.w = silu2(pk[B + 6], m16, mhi);
  asm volatile("st.global.v4.b32 [%0], {%1,%2,%3,%4};" :: "l"(hp + (P & 1) * 8 * FF + 32 * (P >> 1)), "r"(r.x), "r"(r.y), "r"(r.z), "r"(r.w) : "memory");
}
template <int P0, int N>
__device__ __forceinline__ void k4_epi_n(const uint32_t (&pk)[48], uint32_t go, bf16* hp) {
  if constexpr (N > 0) { k4_epi<P0>(pk, go, hp); k4_epi_n<P0 + 1, N - 1>(pk, go, hp); }
}
__host__ __device__ constexpr int k4_first(int i) { return (i * 12 + 8) / 9; }

template <int T, int I>
__device__ __forceinline__ void k4_steps(float (&acc)[96], const uint32_t (&pk)[48], uint64_t da0, uint64_t db0, uint32_t ba, uint32_t bbf,
                                         uint32_t rbe, int wtid, bf16* hp) {
  if constexpr (I < K4_SPT) {
    constexpr int st = T * K4_SPT + I, s = st % K4_NST, k0 = I * K4_KS;
    if (T == 0 && (k0 & 3) == 0) mbar_wait(ba + 8 * (k0 >> 2), 0);
    mbar_wait(bbf + 8 * s, (st / K4_NST) & 1);
    wg_fence();
#pragma unroll
    for (int j = 0; j < K4_KS; j++)
      wgmma_ss_n192_tb(acc, da0 + (uint64_t)(((k0 + j) >> 2) * 1024 + ((k0 + j) & 3) * 2), db0 + (uint64_t)(s * (K4_STB / 16) + j * 128), (I | j) != 0);
    wg_commit();
    if (I > 0) {
      wg_wait<1>();
      if (st - 1 + K4_NST < 3 * K4_SPT && wtid < 2) mbar_arrive_remote(rbe + 8 * ((st - 1) % K4_NST));
    }
    if constexpr (T > 0 && k4_first(I + 1) > k4_first(I)) {
      const uint32_t go = mbar_try(ba, 0);
      k4_epi_n<k4_first(I), k4_first(I + 1) - k4_first(I)>(pk, go, hp);
    }
    k4_steps<T, I + 1>(acc, pk, da0, db0, ba, bbf, rbe, wtid, hp);
  }
}
template <int T>
__device__ __forceinline__ void k4_tile(float (&acc)[96], const uint32_t (&pk)[48], uint64_t da0, uint64_t db0, uint32_t ba, uint32_t bbf,
                                        uint32_t rbe, int wtid, bf16* hprev) {
  k4_steps<T, 0>(acc, pk, da0, db0, ba, bbf, rbe, wtid, hprev);
  wg_wait<0>();
  fence_regs(acc);
  if (T * K4_SPT + K4_SPT - 1 + K4_NST < 3 * K4_SPT && wtid < 2) mbar_arrive_remote(rbe + 8 * ((T * K4_SPT + K4_SPT - 1) % K4_NST));
}
__device__ __forceinline__ void k4_pack(const float (&acc)[96], uint32_t (&pk)[48]) {
#pragma unroll
  for (int i = 0; i < 48; i++) pk[i] = pack_bf16(acc[2 * i], acc[2 * i + 1]);
}

__global__ void __launch_bounds__(384, 1) k4_mlp1(const __grid_constant__ CUtensorMap tm_h2, const __grid_constant__ CUtensorMap tm_w1) {
  extern __shared__ __align__(1024) uint8_t smem[];
  const uint32_t sb = s2u(smem);
  const int tid = threadIdx.x, rb = blockIdx.x & 15, fs = blockIdx.x >> 4;
  const uint32_t ba = sb + K4_BAR, bbf = ba + 72, bbe = bbf + 8 * K4_NST;
  TL(4, 0);
  if (tid == 0) {
    for (int i = 0; i < 9; i++) mbar_init(ba + 8 * i, 1);
    for (int i = 0; i < K4_NST; i++) { mbar_init(bbf + 8 * i, 1); mbar_init(bbe + 8 * i, 4); }
    fence_barrier_init();
    tmap_prefetch(&tm_h2); tmap_prefetch(&tm_w1);
  }
  __syncthreads();
  cluster_arrive_relaxed();
  pdl_launch();
  if (tid < 128) {
    reg_dec<40>();
    if (tid >= 32 && tid < 64) {
      if (tid == 32) {
        pdl_wait();
        for (int c = 0; c < 9; c++) {
          if (c >= 4) mbar_wait(ba + 8 * (c - 4), 0);
          mbar_expect(ba + 8 * c, 16384); tma2d(sb + K4_A + c * 16384, &tm_h2, c * 64, rb * 128, ba + 8 * c);
        }
      }
      __syncwarp();
      cluster_wait();
    } else {
      cluster_wait();
      if (tid == 0) {
        const int rank = cluster_rank();
        for (int st = 0; st < 3 * K4_SPT; st++) {
          const int s = st % K4_NST, t = st / K4_SPT, i = st % K4_SPT;
          if (st >= K4_NST) mbar_wait(bbe + 8 * s, (st / K4_NST - 1) & 1);
          mbar_expect(bbf + 8 * s, K4_STB);
          for (int g = 0; g < 3; g++)
            tma2d_mc(sb + K4_B + s * K4_STB + g * (K4_STB / 3) + rank * (K4_STB / 6), &tm_w1, fs * 576 + t * 192 + g * 64, i * K4_BK + rank * (K4_BK / 2), bbf + 8 * s);
        }
        cluster_arrive_relaxed(); cluster_wait();
      }
    }
  } else {
    reg_inc<232>();
    const int wg = __reduce_max_sync(0xffffffffu, ((unsigned)tid >> 7) - 1), wtid = tid & 127, warp = (tid >> 5) & 3, lane = tid & 31;
    const uint64_t da0 = mkdesc(sb + K4_A + wg * 8192, 16, 1024, 1);
    const uint64_t db0 = mkdesc(sb + K4_B, K4_STB / 3, 1024, 1);
    cluster_wait();
    const uint32_t rbe = map_cta(bbe, wtid & 1);
    bf16* hp = g_H + (size_t)(rb * 128 + wg * 64 + warp * 16 + (lane >> 2)) * FF + fs * 576 + (lane & 3) * 8;
    float acc[96]; uint32_t pk[48];
#pragma unroll
    for (int i = 0; i < 96; i++) acc[i] = 0.f;
    TLT(4, 1, 128); TLC(4, 3, 128);
    k4_tile<0>(acc, pk, da0, db0, ba, bbf, rbe, wtid, hp);
    k4_pack(acc, pk);
    k4_tile<1>(acc, pk, da0, db0, ba, bbf, rbe, wtid, hp);
    k4_pack(acc, pk);
    k4_tile<2>(acc, pk, da0, db0, ba, bbf, rbe, wtid, hp + 192);
    cluster_arrive_relaxed();
    TLT(4, 2, 128); TLC(4, 4, 128);
    k4_pack(acc, pk);
    k4_epi_n<0, 12>(pk, 1u, hp + 384);
    TLT(4, 7, 128);
    cluster_wait();
  }
}

constexpr int K5_NST = 4;
constexpr int K5_STAGE = 16384 + 36864;
constexpr int K5_GB = K5_NST * K5_STAGE, K5_BAR = K5_GB + 576, K5_SMEM = K5_BAR + 8 * (2 * K5_NST + 1);

template <int I> __device__ __forceinline__ float k5_acc(const float (&a)[128], const float (&b)[16]) { if constexpr (I < 128) return a[I]; else return b[I - 128]; }

template <int QD, int I>
__device__ __forceinline__ void k5_stage(const float (&a)[128], const float (&b)[16], uint32_t dst, uint32_t gbs) {
  if constexpr (I < 9) {
    constexpr int B = 9 * QD + I;
    const uint32_t gb = lds32(gbs + B * 16);
    const float g0 = bf_lo(gb), g1 = bf_hi(gb);
    sts32(dst + I * 16, pack_bf16(k5_acc<4 * B>(a, b) * g0, k5_acc<4 * B + 1>(a, b) * g1));
    sts32(dst + 8 * 144 + I * 16, pack_bf16(k5_acc<4 * B + 2>(a, b) * g0, k5_acc<4 * B + 3>(a, b) * g1));
    k5_stage<QD, I + 1>(a, b, dst, gbs);
  }
}
template <int QD>
__device__ __forceinline__ void k5_quarter(const float (&a)[128], const float (&b)[16], uint32_t sb, uint32_t dst, uint32_t gbs, int wg, int wtid,
                                           const CUtensorMap* tm, int col, int row) {
  k5_stage<QD, 0>(a, b, dst + QD * 18432, gbs);
  fence_async_smem();
  bar_sync(2 + wg, 128);
  if (wtid == 0) {
    asm volatile("cp.reduce.async.bulk.tensor.2d.global.shared::cta.add.tile.bulk_group [%0, {%2, %3}], [%1];"
                 :: "l"(tm), "r"(sb + QD * 18432 + wg * 9216), "r"(col + QD * 72), "r"(row) : "memory");
    bulk_commit();
  }
}

__global__ void __launch_bounds__(384, 1) k5_mlp2(const __grid_constant__ CUtensorMap tm_h, const __grid_constant__ CUtensorMap tm_w2,
                                                  const __grid_constant__ CUtensorMap tm_w2n, const __grid_constant__ CUtensorMap tm_out) {
  extern __shared__ __align__(1024) uint8_t smem[];
  const uint32_t sb = s2u(smem);
  const int tid = threadIdx.x, rb = blockIdx.x & 15, nh = (blockIdx.x >> 4) & 1, ks = blockIdx.x >> 5;
  const uint32_t bf = sb + K5_BAR, be = bf + 8 * K5_NST, bg = be + 8 * K5_NST;
  TL(5, 0);
  if (tid == 0) {
    for (int i = 0; i < K5_NST; i++) { mbar_init(bf + 8 * i, 1); mbar_init(be + 8 * i, 4); }
    mbar_init(bg, 1);
    fence_barrier_init();
    tmap_prefetch(&tm_h); tmap_prefetch(&tm_w2); tmap_prefetch(&tm_w2n); tmap_prefetch(&tm_out);
  }
  __syncthreads();
  cluster_arrive_relaxed(); cluster_wait();
  const int rank = cluster_rank();
  if (tid < 128) {
    reg_dec<40>();
    if (tid == 0) {
      auto load_b = [&](int st) {
        const int s = st % K5_NST;
        mbar_expect(bf + 8 * s, K5_STAGE);
        for (int g = 2 * rank; g < 2 * rank + 2; g++)
          tma5d_mc(sb + s * K5_STAGE + 16384 + g * 8192, &tm_w2, nh * 288 + g * 64, 0, 0, 0, (ks * 18 + st) * 2, bf + 8 * s);
        if (rank == 1) tma5d_mc(sb + s * K5_STAGE + 16384 + 32768, &tm_w2n, nh * 288 + 256, 0, 0, 0, (ks * 18 + st) * 2, bf + 8 * s);
      };
      load_b(0);
      pdl_wait();
      for (int st = 0; st < 18; st++) {
        const int s = st % K5_NST;
        if (st >= K5_NST) mbar_wait(be + 8 * s, (st / K5_NST - 1) & 1);
        if (st >= 1) load_b(st);
        tma2d(sb + s * K5_STAGE, &tm_h, (ks * 18 + st) * 64, rb * 128, bf + 8 * s);
        if (st == K5_NST) { mbar_expect(bg, 576); bulk_g2s(sb + K5_GB, g_mod + 5 * DM + nh * 288, 576, bg); }
      }
      cluster_arrive_relaxed(); cluster_wait();
    }
  } else {
    reg_inc<232>();
    const int ctid = tid - 128, wg = __reduce_max_sync(0xffffffffu, (unsigned)ctid >> 7), wtid = tid & 127, warp = (tid >> 5) & 3, lane = tid & 31, g = lane >> 2, q4 = lane & 3;
    float a[128], b[16];
#pragma unroll
    for (int i = 0; i < 128; i++) a[i] = 0.f;
#pragma unroll
    for (int i = 0; i < 16; i++) b[i] = 0.f;
    const uint64_t db0 = mkdesc(sb + 16384, 8192, 1024, 1);
    const uint64_t dn0 = mkdesc(sb + 16384 + 32768, 4096, 512, 2);
    const uint32_t rbe = map_cta(be, wtid & 1);
    uint32_t aoff[4];
    {
      const int r = wg * 64 + warp * 16 + (lane & 7) + ((lane >> 3) & 1) * 8;
#pragma unroll
      for (int j = 0; j < 4; j++) aoff[j] = sb + r * 128 + (((2 * j + (lane >> 4)) ^ (lane & 7)) << 4);
    }
    uint32_t A0[4][4], A1[4][4];
    auto step = [&](uint32_t (&A)[4][4], int st) {
      const int s = st % K5_NST;
      mbar_wait(bf + 8 * s, (st / K5_NST) & 1);
#pragma unroll
      for (int j = 0; j < 4; j++) ldsm4(A[j], aoff[j] + s * K5_STAGE);
      fence_regs(A[0]); fence_regs(A[1]); fence_regs(A[2]); fence_regs(A[3]);
      wg_fence();
#pragma unroll
      for (int j = 0; j < 4; j++) {
        wgmma_rs_n256_tb(a, A[j][0], A[j][1], A[j][2], A[j][3], db0 + (uint64_t)(s * (K5_STAGE / 16) + j * 128), 1);
        wgmma_rs_n32_tb(b, A[j][0], A[j][1], A[j][2], A[j][3], dn0 + (uint64_t)(s * (K5_STAGE / 16) + j * 64), 1);
      }
      wg_commit();
      if (st > 0) {
        wg_wait<1>();
        if (st - 1 + K5_NST < 18 && wtid < 2) mbar_arrive_remote(rbe + 8 * ((st - 1) % K5_NST));
      }
    };
#pragma unroll 1
    for (int st = 0; st < 18; st += 2) { step(A0, st); step(A1, st + 1); }
    wg_wait<0>();
    fence_regs(a); fence_regs(b);
    cluster_arrive_relaxed();
    TLT(5, 2, 128);
    mbar_wait(bg, 0);
    bar_sync(1, 256);
    const uint32_t dst = sb + (wg * 64 + warp * 16 + g) * 144 + q4 * 4, gbs = sb + K5_GB + q4 * 4;
    k5_quarter<0>(a, b, sb, dst, gbs, wg, wtid, &tm_out, nh * 288, rb * 128 + wg * 64);
    k5_quarter<1>(a, b, sb, dst, gbs, wg, wtid, &tm_out, nh * 288, rb * 128 + wg * 64);
    k5_quarter<2>(a, b, sb, dst, gbs, wg, wtid, &tm_out, nh * 288, rb * 128 + wg * 64);
    k5_quarter<3>(a, b, sb, dst, gbs, wg, wtid, &tm_out, nh * 288, rb * 128 + wg * 64);
    TLT(5, 3, 128);
    if (wtid == 0) bulk_wait_read();
    TLT(5, 7, 128);
    cluster_wait();
  }
}

}

typedef CUresult (*EncodeTiledFn)(CUtensorMap*, CUtensorMapDataType, cuuint32_t, void*, const cuuint64_t*, const cuuint64_t*, const cuuint32_t*,
                                  const cuuint32_t*, CUtensorMapInterleave, CUtensorMapSwizzle, CUtensorMapL2promotion, CUtensorMapFloatOOBfill);

static void make_map2d(EncodeTiledFn enc, CUtensorMap* m, const void* base, int cols, int rows, int box_cols, int box_rows, CUtensorMapSwizzle sw) {
  cuuint64_t dims[2] = {(cuuint64_t)cols, (cuuint64_t)rows};
  cuuint64_t strides[1] = {(cuuint64_t)cols * 2};
  cuuint32_t box[2] = {(cuuint32_t)box_cols, (cuuint32_t)box_rows};
  cuuint32_t es[2] = {1, 1};
  enc(m, CU_TENSOR_MAP_DATA_TYPE_BFLOAT16, 2, const_cast<void*>(base), dims, strides, box, es, CU_TENSOR_MAP_INTERLEAVE_NONE, sw,
      CU_TENSOR_MAP_L2_PROMOTION_L2_128B, CU_TENSOR_MAP_FLOAT_OOB_FILL_NONE);
}

template <typename... KArgs, typename... Args>
static void launch(void (*kern)(KArgs...), int grid, int block, int smem, bool pdl, int cluster, Args... args) {
  cudaLaunchConfig_t cfg = {};
  cfg.gridDim = dim3(grid); cfg.blockDim = dim3(block); cfg.dynamicSmemBytes = smem; cfg.stream = cudaStreamPerThread;
  cudaLaunchAttribute at[2];
  int n = 0;
  if (pdl) { at[n].id = cudaLaunchAttributeProgrammaticStreamSerialization; at[n].val.programmaticStreamSerializationAllowed = 1; n++; }
  if (cluster > 1) { at[n].id = cudaLaunchAttributeClusterDimension; at[n].val.clusterDim.x = cluster; at[n].val.clusterDim.y = 1; at[n].val.clusterDim.z = 1; n++; }
  cfg.attrs = at; cfg.numAttrs = n;
  cudaLaunchKernelEx(&cfg, kern, KArgs(args)...);
}

#define USE_PDL 1

extern "C" void kernel_launch(void* const* d_in, const int* in_sizes, int n_in, void* d_out, int out_size) {
  (void)in_sizes; (void)n_in; (void)out_size;
  const bf16* x    = (const bf16*)d_in[0];
  const bf16* wqkv = (const bf16*)d_in[1];
  const bf16* wo   = (const bf16*)d_in[2];
  const bf16* w1   = (const bf16*)d_in[4];
  const bf16* w2   = (const bf16*)d_in[5];
  const bf16* c    = (const bf16*)d_in[6];
  const bf16* wmod = (const bf16*)d_in[7];
  bf16* out = (bf16*)d_out;

  static EncodeTiledFn enc = nullptr;
  if (!enc) {
    void* fn = nullptr; cudaDriverEntryPointQueryResult qr;
    cudaGetDriverEntryPoint("cuTensorMapEncodeTiled", &fn, cudaEnableDefault, &qr);
    enc = (EncodeTiledFn)fn;
    cudaFuncSetAttribute(k1_qkv, cudaFuncAttributeMaxDynamicSharedMemorySize, K1_SMEM);
    cudaFuncSetAttribute(k2_attn, cudaFuncAttributeMaxDynamicSharedMemorySize, K2_SMEM);
    cudaFuncSetAttribute(k3_wo, cudaFuncAttributeMaxDynamicSharedMemorySize, K3_SMEM);
    cudaFuncSetAttribute(k4_mlp1, cudaFuncAttributeMaxDynamicSharedMemorySize, K4_SMEM);
    cudaFuncSetAttribute(k5_mlp2, cudaFuncAttributeMaxDynamicSharedMemorySize, K5_SMEM);
  }
  void *p_arena, *p_woT;
  cudaGetSymbolAddress(&p_arena, g_arena); cudaGetSymbolAddress(&p_woT, g_woT);
  void* p_h2 = p_arena;
  void* p_xn = (uint8_t*)p_arena + 96 * SLOT_BYTES;
  void* p_o = p_xn;
  void* p_H = (uint8_t*)p_arena + ACT_BYTES;
  CUtensorMap tm_xn, tm_wqkv, tm_o, tm_wo, tm_x, tm_x2s, tm_h2s, tm_h2, tm_w1, tm_H, tm_w2, tm_w2n, tm_out, tm_wmod;
  make_map2d(enc, &tm_xn, p_xn, DM, SEQ, 64, 128, CU_TENSOR_MAP_SWIZZLE_128B);
  make_map2d(enc, &tm_wqkv, wqkv, 3 * DM, DM, 64, 32, CU_TENSOR_MAP_SWIZZLE_128B);
  make_map2d(enc, &tm_o, p_o, DM, SEQ, 64, 64, CU_TENSOR_MAP_SWIZZLE_128B);
  make_map2d(enc, &tm_x, x, DM, SEQ, 72, 128, CU_TENSOR_MAP_SWIZZLE_NONE);
  make_map2d(enc, &tm_wmod, wmod, 6 * DM, DM, 192, 64, CU_TENSOR_MAP_SWIZZLE_NONE);
  make_map2d(enc, &tm_x2s, out, DM, SEQ, 72, 128, CU_TENSOR_MAP_SWIZZLE_NONE);
  make_map2d(enc, &tm_out, out, DM, SEQ, 72, 64, CU_TENSOR_MAP_SWIZZLE_NONE);
  make_map2d(enc, &tm_h2s, p_h2, DM, SEQ, 72, 128, CU_TENSOR_MAP_SWIZZLE_NONE);
  make_map2d(enc, &tm_wo, p_woT, DM, DM, 64, 72, CU_TENSOR_MAP_SWIZZLE_128B);
  make_map2d(enc, &tm_h2, p_h2, DM, SEQ, 64, 128, CU_TENSOR_MAP_SWIZZLE_128B);
  make_map2d(enc, &tm_w1, w1, FF, DM, 64, K4_BK / 2, CU_TENSOR_MAP_SWIZZLE_128B);
  make_map2d(enc, &tm_H, p_H, FF, SEQ, 64, 128, CU_TENSOR_MAP_SWIZZLE_128B);
  for (int narrow = 0; narrow < 2; narrow++) {
    cuuint64_t dims[5] = {(cuuint64_t)DM, 2, 4, 4, (cuuint64_t)(FF / 32)};
    cuuint64_t strides[4] = {(cuuint64_t)DM * 2, (cuuint64_t)DM * 2 * 8, (cuuint64_t)DM * 2 * 2, (cuuint64_t)DM * 2 * 32};
    cuuint32_t box[5] = {narrow ? 32u : 64u, 2, 4, 4, 2};
    cuuint32_t es[5] = {1, 1, 1, 1, 1};
    enc(narrow ? &tm_w2n : &tm_w2, CU_TENSOR_MAP_DATA_TYPE_BFLOAT16, 5, const_cast<bf16*>(w2), dims, strides, box, es, CU_TENSOR_MAP_INTERLEAVE_NONE,
        narrow ? CU_TENSOR_MAP_SWIZZLE_64B : CU_TENSOR_MAP_SWIZZLE_128B, CU_TENSOR_MAP_L2_PROMOTION_L2_128B, CU_TENSOR_MAP_FLOAT_OOB_FILL_NONE);
  }
  launch(k0_mod_ln, 36 * MODP + 128, 256, 0, false, 1, x, c, wmod);
  launch(k1_qkv, 128, 352, K1_SMEM, USE_PDL, 2, tm_xn, tm_wqkv, wo);
  launch(k2_attn, 132, 512, K2_SMEM, USE_PDL, 1, tm_wmod, c, w1, w2);
  launch(k3_wo, 128, 320, K3_SMEM, USE_PDL, 2, tm_o, tm_wo, tm_x, tm_x2s, tm_h2s);
  launch(k4_mlp1, 128, 384, K4_SMEM, USE_PDL, 2, tm_h2, tm_w1);
  launch(k5_mlp2, 128, 384, K5_SMEM, USE_PDL, 2, tm_H, tm_w2, tm_w2n, tm_out);
}
```

```cpp
#include <cuda_runtime.h>
#include <cuda_bf16.h>
#include <cuda.h>
#include <stdint.h>

namespace {

constexpr int SEQ = 2048, DM = 576, DHEAD = 18, FF = 4608;
constexpr int SLOT_BYTES = SEQ * 48;

typedef __nv_bfloat16 bf16;

__device__ __align__(1024) bf16    g_mod[6 * DM];
#define MODP 2
__device__ __align__(1024) float   g_modp[MODP * 2 * DM];
constexpr int ACT_BYTES = SEQ * DM * 2;
__device__ __align__(1024) uint8_t g_arena[ACT_BYTES + SEQ * FF * 2];
#define g_qkvp (g_arena)
#define g_h2   (reinterpret_cast<bf16*>(g_arena))
#define g_xn   (reinterpret_cast<bf16*>(g_arena + 96 * SLOT_BYTES))
#define g_o    (reinterpret_cast<bf16*>(g_arena + 96 * SLOT_BYTES))
#define g_H    (reinterpret_cast<bf16*>(g_arena + ACT_BYTES))
__device__ __align__(1024) float   g_nrm[64 * 16];
__device__ __align__(1024) bf16    g_woT[DM * DM];
__device__ __align__(1024) uint4   g_stats[SEQ * 8];
__device__ unsigned int g_epoch;

__device__ __forceinline__ uint32_t s2u(const void* p) { return (uint32_t)__cvta_generic_to_shared(p); }
__device__ __forceinline__ void mbar_init(uint32_t b, uint32_t c) { asm volatile("mbarrier.init.shared::cta.b64 [%0], %1;" :: "r"(b), "r"(c) : "memory"); }
__device__ __forceinline__ void mbar_expect(uint32_t b, uint32_t bytes) { asm volatile("mbarrier.arrive.expect_tx.shared::cta.b64 _, [%0], %1;" :: "r"(b), "r"(bytes) : "memory"); }
__device__ __forceinline__ void mbar_arrive(uint32_t b) { asm volatile("mbarrier.arrive.shared::cta.b64 _, [%0];" :: "r"(b) : "memory"); }
__device__ __forceinline__ bool mbar_try(uint32_t b, uint32_t ph) {
  uint32_t ok;
  asm volatile("{\n.reg .pred p;\nmbarrier.try_wait.parity.shared::cta.b64 p, [%1], %2;\nselp.u32 %0, 1, 0, p;\n}" : "=r"(ok) : "r"(b), "r"(ph) : "memory");
  return ok != 0;
}
__device__ __forceinline__ void mbar_wait(uint32_t b, uint32_t ph) {
  if (!mbar_try(b, ph)) {
    for (int n = 0; n < (1 << 22); n++) if (mbar_try(b, ph)) break;
  }
}
__device__ __forceinline__ void fence_barrier_init() { asm volatile("fence.mbarrier_init.release.cluster;" ::: "memory"); }
__device__ __forceinline__ void fence_async_smem() { asm volatile("fence.proxy.async.shared::cta;" ::: "memory"); }
__device__ __forceinline__ void bar_sync(int id, int n) { asm volatile("bar.sync %0, %1;" :: "r"(id), "r"(n) : "memory"); }
__device__ __forceinline__ void pdl_wait() { asm volatile("griddepcontrol.wait;" ::: "memory"); }
__device__ __forceinline__ void pdl_launch() { asm volatile("griddepcontrol.launch_dependents;" ::: "memory"); }
__device__ __forceinline__ void bulk_g2s(uint32_t dst, const void* src, uint32_t bytes, uint32_t bar) {
  asm volatile("cp.async.bulk.shared::cluster.global.mbarrier::complete_tx::bytes [%0], [%1], %2, [%3];" :: "r"(dst), "l"(src), "r"(bytes), "r"(bar) : "memory");
}
__device__ __forceinline__ void bulk_s2g(void* dst, uint32_t src, uint32_t bytes) {
  asm volatile("cp.async.bulk.global.shared::cta.bulk_group [%0], [%1], %2;" :: "l"(dst), "r"(src), "r"(bytes) : "memory");
}
__device__ __forceinline__ void bulk_commit() { asm volatile("cp.async.bulk.commit_group;" ::: "memory"); }
__device__ __forceinline__ void bulk_wait_read() { asm volatile("cp.async.bulk.wait_group.read 0;" ::: "memory"); }
__device__ __forceinline__ void tma2d(uint32_t dst, const CUtensorMap* m, int x, int y, uint32_t bar) {
  asm volatile("cp.async.bulk.tensor.2d.shared::cluster.global.mbarrier::complete_tx::bytes [%0], [%1, {%3, %4}], [%2];"
               :: "r"(dst), "l"(m), "r"(bar), "r"(x), "r"(y) : "memory");
}
__device__ __forceinline__ void tma2d_mc(uint32_t dst, const CUtensorMap* m, int x, int y, uint32_t bar) {
  asm volatile("cp.async.bulk.tensor.2d.shared::cluster.global.mbarrier::complete_tx::bytes.multicast::cluster [%0], [%1, {%3, %4}], [%2], %5;"
               :: "r"(dst), "l"(m), "r"(bar), "r"(x), "r"(y), "h"((uint16_t)3) : "memory");
}
__device__ __forceinline__ void tma5d_mc(uint32_t dst, const CUtensorMap* m, int c0, int c1, int c2, int c3, int c4, uint32_t bar) {
  asm volatile("cp.async.bulk.tensor.5d.shared::cluster.global.mbarrier::complete_tx::bytes.multicast::cluster [%0], [%1, {%3, %4, %5, %6, %7}], [%2], %8;"
               :: "r"(dst), "l"(m), "r"(bar), "r"(c0), "r"(c1), "r"(c2), "r"(c3), "r"(c4), "h"((uint16_t)3) : "memory");
}
__device__ __forceinline__ void tma2d_store(const CUtensorMap* m, uint32_t src, int x, int y) {
  asm volatile("cp.async.bulk.tensor.2d.global.shared::cta.bulk_group [%0, {%2, %3}], [%1];" :: "l"(m), "r"(src), "r"(x), "r"(y) : "memory");
}
__device__ __forceinline__ uint32_t map_cta(uint32_t a, uint32_t cta) { uint32_t r; asm("mapa.shared::cluster.u32 %0, %1, %2;" : "=r"(r) : "r"(a), "r"(cta)); return r; }
__device__ __forceinline__ void mbar_arrive_remote(uint32_t ra) { asm volatile("mbarrier.arrive.shared::cluster.b64 _, [%0];" :: "r"(ra) : "memory"); }
__device__ __forceinline__ void cluster_arrive_relaxed() { asm volatile("barrier.cluster.arrive.relaxed;" ::: "memory"); }
__device__ __forceinline__ void cluster_wait() { asm volatile("barrier.cluster.wait.acquire;" ::: "memory"); }
__device__ __forceinline__ uint32_t cluster_rank() { uint32_t r; asm("mov.u32 %0, %%cluster_ctarank;" : "=r"(r)); return r; }
__device__ __forceinline__ void tma2d_prefetch(const CUtensorMap* m, int x, int y) {
  asm volatile("cp.async.bulk.prefetch.tensor.2d.L2.global [%0, {%1, %2}];" :: "l"(m), "r"(x), "r"(y) : "memory");
}
__device__ __forceinline__ void tmap_prefetch(const CUtensorMap* m) { asm volatile("prefetch.tensormap [%0];" :: "l"(m) : "memory"); }
__device__ __forceinline__ void wg_fence() { asm volatile("wgmma.fence.sync.aligned;" ::: "memory"); }
__device__ __forceinline__ void wg_commit() { asm volatile("wgmma.commit_group.sync.aligned;" ::: "memory"); }
template <int N> __device__ __forceinline__ void wg_wait() { asm volatile("wgmma.wait_group.sync.aligned %0;" :: "n"(N) : "memory"); }
__device__ __forceinline__ uint64_t mkdesc(uint32_t addr, uint32_t lbo, uint32_t sbo, int sw) {
  return (uint64_t)((addr & 0x3FFFF) >> 4) | ((uint64_t)(lbo >> 4) << 16) | ((uint64_t)(sbo >> 4) << 32) | ((uint64_t)sw << 62);
}
template <int N> __device__ __forceinline__ void fence_regs(float (&d)[N]) {
#pragma unroll
  for (int i = 0; i < N; i++) asm volatile("" : "+f"(d[i]) :: "memory");
}
template <int N> __device__ __forceinline__ void fence_regs(uint32_t (&d)[N]) {
#pragma unroll
  for (int i = 0; i < N; i++) asm volatile("" : "+r"(d[i]) :: "memory");
}
__device__ __forceinline__ float ex2(float x) { float y; asm("ex2.approx.ftz.f32 %0, %1;" : "=f"(y) : "f"(x)); return y; }
__device__ __forceinline__ float tanh_fast(float x) { float y; asm("tanh.approx.f32 %0, %1;" : "=f"(y) : "f"(x)); return y; }
__device__ __forceinline__ uint32_t pack_bf16(float lo, float hi) { uint32_t v; asm("cvt.rn.bf16x2.f32 %0, %1, %2;" : "=r"(v) : "f"(hi), "f"(lo)); return v; }
__device__ __forceinline__ float bf_lo(uint32_t v) { return __uint_as_float(v << 16); }
__device__ __forceinline__ float bf_hi(uint32_t v) { return __uint_as_float(v & 0xFFFF0000u); }
__device__ __forceinline__ float bf_round(float x) { return __bfloat162float(__float2bfloat16_rn(x)); }
__device__ __forceinline__ uint32_t hfma2(uint32_t a, uint32_t b, uint32_t c) { uint32_t d; asm("fma.rn.bf16x2 %0, %1, %2, %3;" : "=r"(d) : "r"(a), "r"(b), "r"(c)); return d; }
__device__ __forceinline__ uint32_t hadd2(uint32_t a, uint32_t b) { uint32_t d; asm("add.rn.bf16x2 %0, %1, %2;" : "=r"(d) : "r"(a), "r"(b)); return d; }
__device__ __forceinline__ uint32_t opaque(uint32_t v) { uint32_t r; asm volatile("mov.b32 %0, %1;" : "=r"(r) : "r"(v)); return r; }
__device__ __forceinline__ void ldsm4(uint32_t (&r)[4], uint32_t a) {
  asm volatile("ldmatrix.sync.aligned.m8n8.x4.shared.b16 {%0,%1,%2,%3}, [%4];" : "=r"(r[0]), "=r"(r[1]), "=r"(r[2]), "=r"(r[3]) : "r"(a));
}
__device__ __forceinline__ uint4 lds128(uint32_t a) { uint4 v; asm volatile("ld.shared.v4.b32 {%0,%1,%2,%3}, [%4];" : "=r"(v.x), "=r"(v.y), "=r"(v.z), "=r"(v.w) : "r"(a)); return v; }
__device__ __forceinline__ uint32_t lds32(uint32_t a) { uint32_t v; asm volatile("ld.shared.b32 %0, [%1];" : "=r"(v) : "r"(a)); return v; }
__device__ __forceinline__ void sts32(uint32_t a, uint32_t v) { asm volatile("st.shared.b32 [%0], %1;" :: "r"(a), "r"(v) : "memory"); }
template <int R> __device__ __forceinline__ void reg_inc() { asm volatile("setmaxnreg.inc.sync.aligned.u32 %0;" :: "n"(R)); }
template <int R> __device__ __forceinline__ void reg_dec() { asm volatile("setmaxnreg.dec.sync.aligned.u32 %0;" :: "n"(R)); }

#define TL(k, i)
#define TLT(k, i, t)
#define TLC(k, i, t)

__device__ __forceinline__ void wgmma_rs_n216_tb(float (&d)[108], uint32_t a0, uint32_t a1, uint32_t a2, uint32_t a3, uint64_t db, int sd) {
  asm volatile("{\n.reg .pred p;\nsetp.ne.b32 p, %113, 0;\n"
    "wgmma.mma_async.sync.aligned.m64n216k16.f32.bf16.bf16 "
    "{%0, %1, %2, %3, %4, %5, %6, %7, %8, %9, %10, %11, %12, %13, %14, %15, %16, %17, %18, %19, %20, %21, %22, %23, %24, %25, %26, %27, %28, %29, %30, %31, %32, %33, %34, %35, %36, %37, %38, %39, %40, %41, %42, %43, %44, %45, %46, %47, %48, %49, %50, %51, %52, %53, %54, %55, %56, %57, %58, %59, %60, %61, %62, %63, %64, %65, %66, %67, %68, %69, %70, %71, %72, %73, %74, %75, %76, %77, %78, %79, %80, %81, %82, %83, %84, %85, %86, %87, %88, %89, %90, %91, %92, %93, %94, %95, %96, %97, %98, %99, %100, %101, %102, %103, %104, %105, %106, %107}, {%108,%109,%110,%111}, %112, p, 1, 1, 1;\n}\n"
    : "+f"(d[0]), "+f"(d[1]), "+f"(d[2]), "+f"(d[3]), "+f"(d[4]), "+f"(d[5]), "+f"(d[6]), "+f"(d[7]), "+f"(d[8]), "+f"(d[9]), "+f"(d[10]), "+f"(d[11]), "+f"(d[12]), "+f"(d[13]), "+f"(d[14]), "+f"(d[15]), "+f"(d[16]), "+f"(d[17]), "+f"(d[18]), "+f"(d[19]), "+f"(d[20]), "+f"(d[21]), "+f"(d[22]), "+f"(d[23]), "+f"(d[24]), "+f"(d[25]), "+f"(d[26]), "+f"(d[27]), "+f"(d[28]), "+f"(d[29]), "+f"(d[30]), "+f"(d[31]), "+f"(d[32]), "+f"(d[33]), "+f"(d[34]), "+f"(d[35]), "+f"(d[36]), "+f"(d[37]), "+f"(d[38]), "+f"(d[39]), "+f"(d[40]), "+f"(d[41]), "+f"(d[42]), "+f"(d[43]), "+f"(d[44]), "+f"(d[45]), "+f"(d[46]), "+f"(d[47]), "+f"(d[48]), "+f"(d[49]), "+f"(d[50]), "+f"(d[51]), "+f"(d[52]), "+f"(d[53]), "+f"(d[54]), "+f"(d[55]), "+f"(d[56]), "+f"(d[57]), "+f"(d[58]), "+f"(d[59]), "+f"(d[60]), "+f"(d[61]), "+f"(d[62]), "+f"(d[63]), "+f"(d[64]), "+f"(d[65]), "+f"(d[66]), "+f"(d[67]), "+f"(d[68]), "+f"(d[69]), "+f"(d[70]), "+f"(d[71]), "+f"(d[72]), "+f"(d[73]), "+f"(d[74]), "+f"(d[75]), "+f"(d[76]), "+f"(d[77]), "+f"(d[78]), "+f"(d[79]), "+f"(d[80]), "+f"(d[81]), "+f"(d[82]), "+f"(d[83]), "+f"(d[84]), "+f"(d[85]), "+f"(d[86]), "+f"(d[87]), "+f"(d[88]), "+f"(d[89]), "+f"(d[90]), "+f"(d[91]), "+f"(d[92]), "+f"(d[93]), "+f"(d[94]), "+f"(d[95]), "+f"(d[96]), "+f"(d[97]), "+f"(d[98]), "+f"(d[99]), "+f"(d[100]), "+f"(d[101]), "+f"(d[102]), "+f"(d[103]), "+f"(d[104]), "+f"(d[105]), "+f"(d[106]), "+f"(d[107])
    : "r"(a0), "r"(a1), "r"(a2), "r"(a3), "l"(db), "r"(sd));
}
__device__ __forceinline__ void wgmma_ss_n72(float (&d)[36], uint64_t da, uint64_t db, int sd) {
  asm volatile("{\n.reg .pred p;\nsetp.ne.b32 p, %38, 0;\n"
    "wgmma.mma_async.sync.aligned.m64n72k16.f32.bf16.bf16 "
    "{%0, %1, %2, %3, %4, %5, %6, %7, %8, %9, %10, %11, %12, %13, %14, %15, %16, %17, %18, %19, %20, %21, %22, %23, %24, %25, %26, %27, %28, %29, %30, %31, %32, %33, %34, %35}, %36, %37, p, 1, 1, 0, 0;\n}\n"
    : "+f"(d[0]), "+f"(d[1]), "+f"(d[2]), "+f"(d[3]), "+f"(d[4]), "+f"(d[5]), "+f"(d[6]), "+f"(d[7]), "+f"(d[8]), "+f"(d[9]), "+f"(d[10]), "+f"(d[11]), "+f"(d[12]), "+f"(d[13]), "+f"(d[14]), "+f"(d[15]), "+f"(d[16]), "+f"(d[17]), "+f"(d[18]), "+f"(d[19]), "+f"(d[20]), "+f"(d[21]), "+f"(d[22]), "+f"(d[23]), "+f"(d[24]), "+f"(d[25]), "+f"(d[26]), "+f"(d[27]), "+f"(d[28]), "+f"(d[29]), "+f"(d[30]), "+f"(d[31]), "+f"(d[32]), "+f"(d[33]), "+f"(d[34]), "+f"(d[35])
    : "l"(da), "l"(db), "r"(sd));
}
__device__ __forceinline__ void wgmma_ss_n192_tb(float (&d)[96], uint64_t da, uint64_t db, int sd) {
  asm volatile("{\n.reg .pred p;\nsetp.ne.b32 p, %98, 0;\n"
    "wgmma.mma_async.sync.aligned.m64n192k16.f32.bf16.bf16 "
    "{%0, %1, %2, %3, %4, %5, %6, %7, %8, %9, %10, %11, %12, %13, %14, %15, %16, %17, %18, %19, %20, %21, %22, %23, %24, %25, %26, %27, %28, %29, %30, %31, %32, %33, %34, %35, %36, %37, %38, %39, %40, %41, %42, %43, %44, %45, %46, %47, %48, %49, %50, %51, %52, %53, %54, %55, %56, %57, %58, %59, %60, %61, %62, %63, %64, %65, %66, %67, %68, %69, %70, %71, %72, %73, %74, %75, %76, %77, %78, %79, %80, %81, %82, %83, %84, %85, %86, %87, %88, %89, %90, %91, %92, %93, %94, %95}, %96, %97, p, 1, 1, 0, 1;\n}\n"
    : "+f"(d[0]), "+f"(d[1]), "+f"(d[2]), "+f"(d[3]), "+f"(d[4]), "+f"(d[5]), "+f"(d[6]), "+f"(d[7]), "+f"(d[8]), "+f"(d[9]), "+f"(d[10]), "+f"(d[11]), "+f"(d[12]), "+f"(d[13]), "+f"(d[14]), "+f"(d[15]), "+f"(d[16]), "+f"(d[17]), "+f"(d[18]), "+f"(d[19]), "+f"(d[20]), "+f"(d[21]), "+f"(d[22]), "+f"(d[23]), "+f"(d[24]), "+f"(d[25]), "+f"(d[26]), "+f"(d[27]), "+f"(d[28]), "+f"(d[29]), "+f"(d[30]), "+f"(d[31]), "+f"(d[32]), "+f"(d[33]), "+f"(d[34]), "+f"(d[35]), "+f"(d[36]), "+f"(d[37]), "+f"(d[38]), "+f"(d[39]), "+f"(d[40]), "+f"(d[41]), "+f"(d[42]), "+f"(d[43]), "+f"(d[44]), "+f"(d[45]), "+f"(d[46]), "+f"(d[47]), "+f"(d[48]), "+f"(d[49]), "+f"(d[50]), "+f"(d[51]), "+f"(d[52]), "+f"(d[53]), "+f"(d[54]), "+f"(d[55]), "+f"(d[56]), "+f"(d[57]), "+f"(d[58]), "+f"(d[59]), "+f"(d[60]), "+f"(d[61]), "+f"(d[62]), "+f"(d[63]), "+f"(d[64]), "+f"(d[65]), "+f"(d[66]), "+f"(d[67]), "+f"(d[68]), "+f"(d[69]), "+f"(d[70]), "+f"(d[71]), "+f"(d[72]), "+f"(d[73]), "+f"(d[74]), "+f"(d[75]), "+f"(d[76]), "+f"(d[77]), "+f"(d[78]), "+f"(d[79]), "+f"(d[80]), "+f"(d[81]), "+f"(d[82]), "+f"(d[83]), "+f"(d[84]), "+f"(d[85]), "+f"(d[86]), "+f"(d[87]), "+f"(d[88]), "+f"(d[89]), "+f"(d[90]), "+f"(d[91]), "+f"(d[92]), "+f"(d[93]), "+f"(d[94]), "+f"(d[95])
    : "l"(da), "l"(db), "r"(sd));
}
__device__ __forceinline__ void wgmma_rs_n256_tb(float (&d)[128], uint32_t a0, uint32_t a1, uint32_t a2, uint32_t a3, uint64_t db, int sd) {
  asm volatile("{\n.reg .pred p;\nsetp.ne.b32 p, %133, 0;\n"
    "wgmma.mma_async.sync.aligned.m64n256k16.f32.bf16.bf16 "
    "{%0, %1, %2, %3, %4, %5, %6, %7, %8, %9, %10, %11, %12, %13, %14, %15, %16, %17, %18, %19, %20, %21, %22, %23, %24, %25, %26, %27, %28, %29, %30, %31, %32, %33, %34, %35, %36, %37, %38, %39, %40, %41, %42, %43, %44, %45, %46, %47, %48, %49, %50, %51, %52, %53, %54, %55, %56, %57, %58, %59, %60, %61, %62, %63, %64, %65, %66, %67, %68, %69, %70, %71, %72, %73, %74, %75, %76, %77, %78, %79, %80, %81, %82, %83, %84, %85, %86, %87, %88, %89, %90, %91, %92, %93, %94, %95, %96, %97, %98, %99, %100, %101, %102, %103, %104, %105, %106, %107, %108, %109, %110, %111, %112, %113, %114, %115, %116, %117, %118, %119, %120, %121, %122, %123, %124, %125, %126, %127}, {%128,%129,%130,%131}, %132, p, 1, 1, 1;\n}\n"
    : "+f"(d[0]), "+f"(d[1]), "+f"(d[2]), "+f"(d[3]), "+f"(d[4]), "+f"(d[5]), "+f"(d[6]), "+f"(d[7]), "+f"(d[8]), "+f"(d[9]), "+f"(d[10]), "+f"(d[11]), "+f"(d[12]), "+f"(d[13]), "+f"(d[14]), "+f"(d[15]), "+f"(d[16]), "+f"(d[17]), "+f"(d[18]), "+f"(d[19]), "+f"(d[20]), "+f"(d[21]), "+f"(d[22]), "+f"(d[23]), "+f"(d[24]), "+f"(d[25]), "+f"(d[26]), "+f"(d[27]), "+f"(d[28]), "+f"(d[29]), "+f"(d[30]), "+f"(d[31]), "+f"(d[32]), "+f"(d[33]), "+f"(d[34]), "+f"(d[35]), "+f"(d[36]), "+f"(d[37]), "+f"(d[38]), "+f"(d[39]), "+f"(d[40]), "+f"(d[41]), "+f"(d[42]), "+f"(d[43]), "+f"(d[44]), "+f"(d[45]), "+f"(d[46]), "+f"(d[47]), "+f"(d[48]), "+f"(d[49]), "+f"(d[50]), "+f"(d[51]), "+f"(d[52]), "+f"(d[53]), "+f"(d[54]), "+f"(d[55]), "+f"(d[56]), "+f"(d[57]), "+f"(d[58]), "+f"(d[59]), "+f"(d[60]), "+f"(d[61]), "+f"(d[62]), "+f"(d[63]), "+f"(d[64]), "+f"(d[65]), "+f"(d[66]), "+f"(d[67]), "+f"(d[68]), "+f"(d[69]), "+f"(d[70]), "+f"(d[71]), "+f"(d[72]), "+f"(d[73]), "+f"(d[74]), "+f"(d[75]), "+f"(d[76]), "+f"(d[77]), "+f"(d[78]), "+f"(d[79]), "+f"(d[80]), "+f"(d[81]), "+f"(d[82]), "+f"(d[83]), "+f"(d[84]), "+f"(d[85]), "+f"(d[86]), "+f"(d[87]), "+f"(d[88]), "+f"(d[89]), "+f"(d[90]), "+f"(d[91]), "+f"(d[92]), "+f"(d[93]), "+f"(d[94]), "+f"(d[95]), "+f"(d[96]), "+f"(d[97]), "+f"(d[98]), "+f"(d[99]), "+f"(d[100]), "+f"(d[101]), "+f"(d[102]), "+f"(d[103]), "+f"(d[104]), "+f"(d[105]), "+f"(d[106]), "+f"(d[107]), "+f"(d[108]), "+f"(d[109]), "+f"(d[110]), "+f"(d[111]), "+f"(d[112]), "+f"(d[113]), "+f"(d[114]), "+f"(d[115]), "+f"(d[116]), "+f"(d[117]), "+f"(d[118]), "+f"(d[119]), "+f"(d[120]), "+f"(d[121]), "+f"(d[122]), "+f"(d[123]), "+f"(d[124]), "+f"(d[125]), "+f"(d[126]), "+f"(d[127])
    : "r"(a0), "r"(a1), "r"(a2), "r"(a3), "l"(db), "r"(sd));
}
__device__ __forceinline__ void wgmma_rs_n32_tb(float (&d)[16], uint32_t a0, uint32_t a1, uint32_t a2, uint32_t a3, uint64_t db, int sd) {
  asm volatile("{\n.reg .pred p;\nsetp.ne.b32 p, %21, 0;\n"
    "wgmma.mma_async.sync.aligned.m64n32k16.f32.bf16.bf16 "
    "{%0, %1, %2, %3, %4, %5, %6, %7, %8, %9, %10, %11, %12, %13, %14, %15}, {%16,%17,%18,%19}, %20, p, 1, 1, 1;\n}\n"
    : "+f"(d[0]), "+f"(d[1]), "+f"(d[2]), "+f"(d[3]), "+f"(d[4]), "+f"(d[5]), "+f"(d[6]), "+f"(d[7]), "+f"(d[8]), "+f"(d[9]), "+f"(d[10]), "+f"(d[11]), "+f"(d[12]), "+f"(d[13]), "+f"(d[14]), "+f"(d[15])
    : "r"(a0), "r"(a1), "r"(a2), "r"(a3), "l"(db), "r"(sd));
}
__device__ __forceinline__ void wgmma_rs_n64(float (&d)[32], uint32_t a0, uint32_t a1, uint32_t a2, uint32_t a3, uint64_t db, int sd) {
  asm volatile("{\n.reg .pred p;\nsetp.ne.b32 p, %37, 0;\n"
    "wgmma.mma_async.sync.aligned.m64n64k16.f32.bf16.bf16 "
    "{%0, %1, %2, %3, %4, %5, %6, %7, %8, %9, %10, %11, %12, %13, %14, %15, %16, %17, %18, %19, %20, %21, %22, %23, %24, %25, %26, %27, %28, %29, %30, %31}, {%32,%33,%34,%35}, %36, p, 1, 1, 0;\n}\n"
    : "+f"(d[0]), "+f"(d[1]), "+f"(d[2]), "+f"(d[3]), "+f"(d[4]), "+f"(d[5]), "+f"(d[6]), "+f"(d[7]), "+f"(d[8]), "+f"(d[9]), "+f"(d[10]), "+f"(d[11]), "+f"(d[12]), "+f"(d[13]), "+f"(d[14]), "+f"(d[15]), "+f"(d[16]), "+f"(d[17]), "+f"(d[18]), "+f"(d[19]), "+f"(d[20]), "+f"(d[21]), "+f"(d[22]), "+f"(d[23]), "+f"(d[24]), "+f"(d[25]), "+f"(d[26]), "+f"(d[27]), "+f"(d[28]), "+f"(d[29]), "+f"(d[30]), "+f"(d[31])
    : "r"(a0), "r"(a1), "r"(a2), "r"(a3), "l"(db), "r"(sd));
}
__device__ __forceinline__ void wgmma_rs0_n64(float (&d)[32], uint32_t a0, uint32_t a1, uint32_t a2, uint32_t a3, uint64_t db) {
  asm volatile("{\n.reg .pred p;\nsetp.ne.b32 p, 0, 0;\n"
    "wgmma.mma_async.sync.aligned.m64n64k16.f32.bf16.bf16 "
    "{%0, %1, %2, %3, %4, %5, %6, %7, %8, %9, %10, %11, %12, %13, %14, %15, %16, %17, %18, %19, %20, %21, %22, %23, %24, %25, %26, %27, %28, %29, %30, %31}, {%32,%33,%34,%35}, %36, p, 1, 1, 0;\n}\n"
    : "=f"(d[0]), "=f"(d[1]), "=f"(d[2]), "=f"(d[3]), "=f"(d[4]), "=f"(d[5]), "=f"(d[6]), "=f"(d[7]), "=f"(d[8]), "=f"(d[9]), "=f"(d[10]), "=f"(d[11]), "=f"(d[12]), "=f"(d[13]), "=f"(d[14]), "=f"(d[15]), "=f"(d[16]), "=f"(d[17]), "=f"(d[18]), "=f"(d[19]), "=f"(d[20]), "=f"(d[21]), "=f"(d[22]), "=f"(d[23]), "=f"(d[24]), "=f"(d[25]), "=f"(d[26]), "=f"(d[27]), "=f"(d[28]), "=f"(d[29]), "=f"(d[30]), "=f"(d[31])
    : "r"(a0), "r"(a1), "r"(a2), "r"(a3), "l"(db));
}
__device__ __forceinline__ void wgmma_rs_n24_tb(float (&d)[12], uint32_t a0, uint32_t a1, uint32_t a2, uint32_t a3, uint64_t db, int sd) {
  asm volatile("{\n.reg .pred p;\nsetp.ne.b32 p, %17, 0;\n"
    "wgmma.mma_async.sync.aligned.m64n24k16.f32.bf16.bf16 "
    "{%0, %1, %2, %3, %4, %5, %6, %7, %8, %9, %10, %11}, {%12,%13,%14,%15}, %16, p, 1, 1, 1;\n}\n"
    : "+f"(d[0]), "+f"(d[1]), "+f"(d[2]), "+f"(d[3]), "+f"(d[4]), "+f"(d[5]), "+f"(d[6]), "+f"(d[7]), "+f"(d[8]), "+f"(d[9]), "+f"(d[10]), "+f"(d[11])
    : "r"(a0), "r"(a1), "r"(a2), "r"(a3), "l"(db), "r"(sd));
}

__device__ __forceinline__ float silu_ref(float c) { return bf_round(c / (1.0f + __expf(-c))); }

__global__ void __launch_bounds__(256) k0_mod_ln(const bf16* __restrict__ x, const bf16* __restrict__ c, const bf16* __restrict__ wmod) {
  __shared__ float red[8][32];
  pdl_launch();
  const int t = threadIdx.x, warp = t >> 5, lane = t & 31;
  if (blockIdx.x < 36 * MODP) {
    constexpr int ROWS = DM / MODP, NJ = (ROWS + 63) / 64;
    const int b = blockIdx.x, strip = b % 36, half = b / 36, cq = t & 3, kr = t >> 2;
    if (b == 0 && t == 0) g_epoch = g_epoch + 1;
    uint4 wv[NJ]; float cs[NJ];
#pragma unroll
    for (int j = 0; j < NJ; j++) {
      const int kk = kr + 64 * j, k = half * ROWS + kk;
      if (kk < ROWS) { wv[j] = __ldg(reinterpret_cast<const uint4*>(wmod + (size_t)k * (6 * DM) + strip * 32 + cq * 8)); cs[j] = __bfloat162float(c[k]); }
      else { wv[j] = make_uint4(0, 0, 0, 0); cs[j] = 0.f; }
    }
    float acc[8];
#pragma unroll
    for (int i = 0; i < 8; i++) acc[i] = 0.f;
#pragma unroll
    for (int j = 0; j < NJ; j++) {
      const float s = silu_ref(cs[j]);
      const uint32_t w[4] = {wv[j].x, wv[j].y, wv[j].z, wv[j].w};
#pragma unroll
      for (int i = 0; i < 4; i++) { acc[2 * i] = fmaf(s, bf_lo(w[i]), acc[2 * i]); acc[2 * i + 1] = fmaf(s, bf_hi(w[i]), acc[2 * i + 1]); }
    }
#pragma unroll
    for (int o = 4; o < 32; o <<= 1) {
#pragma unroll
      for (int i = 0; i < 8; i++) acc[i] += __shfl_xor_sync(0xffffffffu, acc[i], o);
    }
    if (lane < 4) {
#pragma unroll
      for (int i = 0; i < 8; i++) red[warp][lane * 8 + i] = acc[i];
    }
    __syncthreads();
    if (t < 32) {
      float s = 0.f;
#pragma unroll
      for (int w = 0; w < 8; w++) s += red[w][t];
      g_modp[half * 1152 + strip * 32 + t] = s;
    }
  } else {
    const int r0 = (blockIdx.x - 36 * MODP) * 16 + warp * 2;
    const uint32_t* xr = reinterpret_cast<const uint32_t*>(x + (size_t)r0 * DM);
    uint32_t xv[2][9];
#pragma unroll
    for (int j = 0; j < 9; j++) { xv[0][j] = __ldg(xr + lane + 32 * j); xv[1][j] = __ldg(xr + 288 + lane + 32 * j); }
    float s0 = 0.f, s1 = 0.f;
#pragma unroll
    for (int j = 0; j < 9; j++) { s0 += bf_lo(xv[0][j]) + bf_hi(xv[0][j]); s1 += bf_lo(xv[1][j]) + bf_hi(xv[1][j]); }
#pragma unroll
    for (int o = 16; o; o >>= 1) { s0 += __shfl_xor_sync(0xffffffffu, s0, o); s1 += __shfl_xor_sync(0xffffffffu, s1, o); }
    const float m0 = s0 * (1.0f / DM), m1 = s1 * (1.0f / DM);
    float v0 = 0.f, v1 = 0.f;
#pragma unroll
    for (int j = 0; j < 9; j++) {
      float d;
      d = bf_lo(xv[0][j]) - m0; v0 = fmaf(d, d, v0); d = bf_hi(xv[0][j]) - m0; v0 = fmaf(d, d, v0);
      d = bf_lo(xv[1][j]) - m1; v1 = fmaf(d, d, v1); d = bf_hi(xv[1][j]) - m1; v1 = fmaf(d, d, v1);
    }
#pragma unroll
    for (int o = 16; o; o >>= 1) { v0 += __shfl_xor_sync(0xffffffffu, v0, o); v1 += __shfl_xor_sync(0xffffffffu, v1, o); }
    const float rs0 = 1.0f / sqrtf(v0 * (1.0f / DM) + 1e-5f), rs1 = 1.0f / sqrtf(v1 * (1.0f / DM) + 1e-5f);
    uint32_t* o32 = reinterpret_cast<uint32_t*>(g_xn + (size_t)r0 * DM);
#pragma unroll
    for (int j = 0; j < 9; j++) {
      o32[lane + 32 * j] = pack_bf16((bf_lo(xv[0][j]) - m0) * rs0, (bf_hi(xv[0][j]) - m0) * rs0);
      o32[288 + lane + 32 * j] = pack_bf16((bf_lo(xv[1][j]) - m1) * rs1, (bf_hi(xv[1][j]) - m1) * rs1);
    }
  }
}

__device__ __forceinline__ void mod_tail(const bf16* __restrict__ c, const CUtensorMap* tm_wmod, int part, uint8_t* smem, uint32_t bar) {
  const int t = threadIdx.x;
  const uint32_t sb = s2u(smem);
  float* sc = reinterpret_cast<float*>(smem + 2 * 73728);
  float* red = sc + 576;
  auto fill = [&](int b) {
    mbar_expect(bar + 8 * (b & 1), 73728);
    for (int j = 0; j < 3; j++) tma2d(sb + (b & 1) * 73728 + j * 24576, tm_wmod, 1152 + part * 576 + j * 192, b * 64, bar + 8 * (b & 1));
  };
  if (t == 0) { fill(0); fill(1); }
  for (int k = t; k < DM; k += 512) sc[k] = silu_ref(__bfloat162float(c[k]));
  __syncthreads();
  const int cg = t % 72, rg = t / 72;
  float acc[8];
#pragma unroll
  for (int i = 0; i < 8; i++) acc[i] = 0.f;
#pragma unroll 1
  for (int b = 0; b < 9; b++) {
    mbar_wait(bar + 8 * (b & 1), (b >> 1) & 1);
    if (rg < 7) {
#pragma unroll 5
      for (int r = rg; r < 64; r += 7) {
        const uint4 v = lds128(sb + (b & 1) * 73728 + (cg / 24) * 24576 + r * 384 + (cg % 24) * 16);
        const float s = sc[b * 64 + r];
        acc[0] = fmaf(s, bf_lo(v.x), acc[0]); acc[1] = fmaf(s, bf_hi(v.x), acc[1]); acc[2] = fmaf(s, bf_lo(v.y), acc[2]); acc[3] = fmaf(s, bf_hi(v.y), acc[3]);
        acc[4] = fmaf(s, bf_lo(v.z), acc[4]); acc[5] = fmaf(s, bf_hi(v.z), acc[5]); acc[6] = fmaf(s, bf_lo(v.w), acc[6]); acc[7] = fmaf(s, bf_hi(v.w), acc[7]);
      }
    }
    __syncthreads();
    if (t == 0 && b + 2 < 9) fill(b + 2);
  }
  if (rg < 7) {
#pragma unroll
    for (int i = 0; i < 8; i++) red[rg * 576 + cg * 8 + i] = acc[i];
  }
  __syncthreads();
  for (int col = t; col < 576; col += 512) {
    float s = 0.f;
#pragma unroll
    for (int r = 0; r < 7; r++) s += red[r * 576 + col];
    g_mod[1152 + part * 576 + col] = __float2bfloat16_rn(s);
  }
}

constexpr int K1_NST = 5;
constexpr int K1_A = 0, K1_W = 147456, K1_MOD = K1_W + K1_NST * 16384, K1_RED = K1_MOD + 2304, K1_BAR = K1_RED + 256;
constexpr int K1_SMEM = K1_BAR + 8 * (10 + 2 * K1_NST);
#define QSCALE (0.23570226039551584f * 1.4426950408889634f)
#define POLY_MASK 0xFC
__host__ __device__ constexpr bool poly_block(int b) {
  return (POLY_MASK >> b) & 1;
}
constexpr uint32_t KPAD_POLY = 0x42FE47C0u;
constexpr uint32_t VPAD_ONE  = 0x00003F80u;

template <int ST>
__device__ __forceinline__ void k1_load_a(uint32_t (&A)[2][4], const uint32_t (&aoff)[4], uint32_t mtab) {
#pragma unroll
  for (int j = 0; j < 2; j++) {
    ldsm4(A[j], aoff[(ST & 1) * 2 + j] + (ST >> 1) * 16384);
    const uint4 m = lds128(mtab + (ST * 2 + j) * 64);
    A[j][0] = hfma2(A[j][0], m.x, m.z); A[j][1] = hfma2(A[j][1], m.x, m.z);
    A[j][2] = hfma2(A[j][2], m.y, m.w); A[j][3] = hfma2(A[j][3], m.y, m.w);
  }
}
template <int ST>
__device__ __forceinline__ void k1_steps(float (&acc)[108], uint32_t (&A)[3][2][4], const uint32_t (&aoff)[4], uint32_t mtab, uint64_t db0,
                                         uint32_t bx, uint32_t bwf, uint32_t rbe, bool releaser) {
  if constexpr (ST < 18) {
    constexpr int s = ST % K1_NST;
    mbar_wait(bwf + 8 * s, (ST / K1_NST) & 1);
    fence_regs(A[ST % 3][0]); fence_regs(A[ST % 3][1]);
    wg_fence();
#pragma unroll
    for (int j = 0; j < 2; j++)
      wgmma_rs_n216_tb(acc, A[ST % 3][j][0], A[ST % 3][j][1], A[ST % 3][j][2], A[ST % 3][j][3], db0 + (uint64_t)(s * 1024 + j * 128), 1);
    wg_commit();
    if constexpr (ST + 1 < 18) {
      if constexpr (((ST + 1) & 1) == 0) mbar_wait(bx + 8 * ((ST + 1) >> 1), 0);
      k1_load_a<ST + 1>(A[(ST + 1) % 3], aoff, mtab);
    }
    if constexpr (ST > 0) {
      wg_wait<1>();
      if (ST - 1 + K1_NST < 18 && releaser) mbar_arrive_remote(rbe + 8 * ((ST - 1) % K1_NST));
    }
    k1_steps<ST + 1>(acc, A, aoff, mtab, db0, bx, bwf, rbe, releaser);
  }
}

__host__ __device__ constexpr int k1_off(int I, int Q) {
  const int col = 8 * I + 2 * Q, sl = col / 18, d = col % 18;
  return sl * 6144 + (d >> 3) * 128 + (d & 7) * 2 - 4 * Q;
}
template <int I>
__device__ __forceinline__ void k1_stage_block(const float (&acc)[108], uint32_t base, int q4, int nq) {
  uint32_t a = base + k1_off(I, 0);
  if constexpr (k1_off(I, 1) != k1_off(I, 0)) a += q4 >= 1 ? k1_off(I, 1) - k1_off(I, 0) : 0;
  if constexpr (k1_off(I, 2) != k1_off(I, 1)) a += q4 >= 2 ? k1_off(I, 2) - k1_off(I, 1) : 0;
  if constexpr (k1_off(I, 3) != k1_off(I, 2)) a += q4 >= 3 ? k1_off(I, 3) - k1_off(I, 2) : 0;
  constexpr int s0 = (8 * I) / 18, s3 = (8 * I + 6) / 18, qs = s0 == s3 ? 4 : (18 * s3 - 8 * I) / 2;
  const float sc = ((q4 >= qs ? s3 : s0) < nq) ? QSCALE : 1.0f;
  sts32(a, pack_bf16(acc[4 * I] * sc, acc[4 * I + 1] * sc));
  sts32(a + 384, pack_bf16(acc[4 * I + 2] * sc, acc[4 * I + 3] * sc));
}
template <int G>
__device__ __forceinline__ void k1_stage_group(const float (&acc)[108], uint32_t base, uint32_t pbase, uint32_t kpad, int q4, int nt, int rb, int tid,
                                               uint32_t sb) {
  const int nq = 32 - 12 * nt;
  k1_stage_block<9 * G + 0>(acc, base, q4, nq); k1_stage_block<9 * G + 1>(acc, base, q4, nq); k1_stage_block<9 * G + 2>(acc, base, q4, nq);
  k1_stage_block<9 * G + 3>(acc, base, q4, nq); k1_stage_block<9 * G + 4>(acc, base, q4, nq); k1_stage_block<9 * G + 5>(acc, base, q4, nq);
  k1_stage_block<9 * G + 6>(acc, base, q4, nq); k1_stage_block<9 * G + 7>(acc, base, q4, nq); k1_stage_block<9 * G + 8>(acc, base, q4, nq);
#pragma unroll
  for (int i = 0; i < 2; i++) {
    const int slot = nt * 12 + 4 * G + 2 * i + (tid >> 7);
    const uint32_t pad = slot >= 64 ? VPAD_ONE : (slot >= 32 ? kpad : 0u);
    const uint32_t a = pbase + (4 * G + 2 * i) * 6144;
    sts32(a + 4, pad);
    asm volatile("st.shared.v2.b32 [%0], {%1, %1};" :: "r"(a + 8), "r"(0u) : "memory");
  }
  fence_async_smem();
  bar_sync(1, 256);
  if (tid == 0) {
#pragma unroll
    for (int sl = 4 * G; sl < 4 * G + 4; sl++)
      bulk_s2g(g_qkvp + (size_t)(nt * 12 + sl) * SLOT_BYTES + (size_t)rb * 6144, sb + sl * 6144, 6144);
    bulk_commit();
  }
}

__device__ __forceinline__ void transpose_wo_block(const bf16* __restrict__ wo, int kb, int nb, int lane) {
  const int h = lane & 1;
  uint4 v[2][8];
#pragma unroll
  for (int u = 0; u < 2; u++)
#pragma unroll
    for (int g = 0; g < 8; g++) v[u][g] = __ldg(reinterpret_cast<const uint4*>(wo + (size_t)(kb * 64 + u * 32 + lane) * DM + nb * 64 + g * 8));
  uint32_t* dst = reinterpret_cast<uint32_t*>(g_woT) + (size_t)(nb * 64 + 4 * h) * (DM / 2) + kb * 32 + (lane >> 1);
#pragma unroll
  for (int u = 0; u < 2; u++)
#pragma unroll
    for (int g = 0; g < 8; g++) {
      const uint32_t r0 = __shfl_xor_sync(0xffffffffu, h ? v[u][g].x : v[u][g].z, 1), r1 = __shfl_xor_sync(0xffffffffu, h ? v[u][g].y : v[u][g].w, 1);
      const uint32_t o0 = h ? v[u][g].z : v[u][g].x, o1 = h ? v[u][g].w : v[u][g].y;
      const uint32_t l0 = h ? r0 : o0, l1 = h ? r1 : o1, h0 = h ? o0 : r0, h1 = h ? o1 : r1;
      uint32_t* d = dst + (size_t)g * 8 * (DM / 2) + u * 16;
      d[0 * (DM / 2)] = __byte_perm(l0, h0, 0x5410); d[1 * (DM / 2)] = __byte_perm(l0, h0, 0x7632);
      d[2 * (DM / 2)] = __byte_perm(l1, h1, 0x5410); d[3 * (DM / 2)] = __byte_perm(l1, h1, 0x7632);
    }
}

__global__ void __launch_bounds__(352, 1) k1_qkv(const __grid_constant__ CUtensorMap tm_xn, const __grid_constant__ CUtensorMap tm_w, const bf16* __restrict__ wo) {
  extern __shared__ __align__(1024) uint8_t smem[];
  const uint32_t sb = s2u(smem);
  const int tid = threadIdx.x, nt = (blockIdx.x >> 1) & 7, rb = (blockIdx.x >> 4) * 2 + (blockIdx.x & 1);
  const uint32_t bx = sb + K1_BAR, bmp = bx + 72, bwf = bmp + 8, bwe = bwf + 8 * K1_NST;
  TL(1, 0);
  if (tid == 256) {
    for (int i = 0; i < 10; i++) mbar_init(bx + 8 * i, 1);
    for (int i = 0; i < K1_NST; i++) { mbar_init(bwf + 8 * i, 1); mbar_init(bwe + 8 * i, 4); }
    fence_barrier_init();
    tmap_prefetch(&tm_xn); tmap_prefetch(&tm_w);
  }
  __syncthreads();
  cluster_arrive_relaxed();
  pdl_launch();
  if (tid >= 320) {
    cluster_wait();
    if (blockIdx.x < 81) transpose_wo_block(wo, blockIdx.x / 9, blockIdx.x % 9, tid & 31);
    return;
  }
  if (tid >= 288) {
    auto load_x = [&](int c) { mbar_expect(bx + 8 * c, 16384); tma2d(sb + K1_A + c * 16384, &tm_xn, c * 64, rb * 128, bx + 8 * c); };
    if (tid == 288) {
      pdl_wait();
      mbar_expect(bmp, MODP * 2 * DM * 4); bulk_g2s(sb + K1_A + 8 * 16384, g_modp, MODP * 2 * DM * 4, bmp);
      load_x(0); load_x(1); load_x(2);
    }
    __syncwarp();
    cluster_wait();
    if (tid == 288)
      for (int c = 3; c < 9; c++) { mbar_wait(bx + 8 * (c - 3), 0); if (c == 8) mbar_wait(bwe, 0); load_x(c); }
    return;
  }
  if (tid >= 256) {
    cluster_wait();
    if (tid == 256) {
      const int rank = cluster_rank();
      auto load_w = [&](int st) {
        const int s = st % K1_NST;
        mbar_expect(bwf + 8 * s, 16384);
        for (int g = 2 * rank; g < 2 * rank + 2; g++) tma2d_mc(sb + K1_W + s * 16384 + g * 4096, &tm_w, nt * 216 + g * 64, st * 32, bwf + 8 * s);
      };
      for (int st = 0; st < K1_NST; st++) load_w(st);
      if (rb < 8) for (int b = rb; b < (18 - K1_NST) * 4; b += 8) tma2d_prefetch(&tm_w, nt * 216 + (b & 3) * 64, (K1_NST + (b >> 2)) * 32);
      for (int st = K1_NST; st < 18; st++) {
        mbar_wait(bwe + 8 * (st % K1_NST), (st / K1_NST - 1) & 1);
        load_w(st);
      }
    }
    __syncwarp();
    cluster_arrive_relaxed(); cluster_wait();
    return;
  }
  cluster_wait();
  const int wg = __reduce_max_sync(0xffffffffu, (unsigned)tid >> 7), wtid = tid & 127, warp = (tid >> 5) & 3, lane = tid & 31, g = lane >> 2, q4 = lane & 3;
  const uint32_t rbe = map_cta(bwe, wtid & 1);
  TL(1, 1);
  {
    const float2* mp = reinterpret_cast<const float2*>(smem + K1_A + 8 * 16384);
    mbar_wait(bmp, 0);
    for (int i = tid; i < 288; i += 256) {
      float2 s0 = mp[i], c0 = mp[288 + i];
#pragma unroll
      for (int p = 1; p < MODP; p++) {
        const float2 s1 = mp[p * 576 + i], c1 = mp[p * 576 + 288 + i];
        s0.x += s1.x; s0.y += s1.y; c0.x += c1.x; c0.y += c1.y;
      }
      const uint32_t a = sb + K1_MOD + (i >> 3) * 64 + (i & 3) * 16 + ((i >> 2) & 1) * 4;
      sts32(a, hadd2(pack_bf16(c0.x, c0.y), 0x3F803F80u));
      sts32(a + 8, pack_bf16(s0.x, s0.y));
    }
  }
  bar_sync(1, 256);
  TL(1, 4);
  uint32_t aoff[4];
  {
    const int r = wg * 64 + warp * 16 + (lane & 7) + ((lane >> 3) & 1) * 8;
#pragma unroll
    for (int j = 0; j < 4; j++) aoff[j] = opaque(sb + K1_A + r * 128 + (((2 * j + (lane >> 4)) ^ (lane & 7)) << 4));
  }
  const uint32_t mtab = opaque(sb + K1_MOD + q4 * 16);
  float acc[108];
#pragma unroll
  for (int i = 0; i < 108; i++) acc[i] = 0.f;
  const uint64_t db0 = mkdesc(sb + K1_W, 4096, 1024, 1);
  uint32_t A[3][2][4];
  mbar_wait(bx, 0);
  TL(1, 5);
  k1_load_a<0>(A[0], aoff, mtab);
  k1_steps<0>(acc, A, aoff, mtab, db0, bx, bwf, rbe, wtid < 2);
  wg_wait<0>();
  fence_regs(acc);
  cluster_arrive_relaxed();
  TL(1, 2);
  bar_sync(1, 256);
  {
    const int tok = wg * 64 + warp * 16 + g;
    const uint32_t base = opaque(sb + (tok >> 3) * 384 + (tok & 7) * 16 + q4 * 4);
    const int tk = tid & 127;
    const uint32_t pbase = opaque(sb + (tid >> 7) * 6144 + (tk >> 3) * 384 + (tk & 7) * 16 + 256);
    const uint32_t kpad = poly_block((tk >> 3) & 7) ? KPAD_POLY : 0u;
    k1_stage_group<0>(acc, base, pbase, kpad, q4, nt, rb, tid, sb);
    k1_stage_group<1>(acc, base, pbase, kpad, q4, nt, rb, tid, sb);
    k1_stage_group<2>(acc, base, pbase, kpad, q4, nt, rb, tid, sb);
  }
  TL(1, 3);
  if (nt * 12 < 64) {
    const int tok = tid & 127;
    float* red = reinterpret_cast<float*>(smem + K1_RED);
#pragma unroll
    for (int i = 0; i < 6; i++) {
      const int sl = (tid >> 7) + 2 * i;
      const uint32_t a = sb + sl * 6144 + (tok >> 3) * 384 + (tok & 7) * 16;
      const uint4 v0 = lds128(a), v1 = lds128(a + 128);
      const uint32_t v2 = lds32(a + 256);
      float n2 = 0.f;
      const uint32_t w[9] = {v0.x, v0.y, v0.z, v0.w, v1.x, v1.y, v1.z, v1.w, v2};
#pragma unroll
      for (int j = 0; j < 9; j++) { n2 = fmaf(bf_lo(w[j]), bf_lo(w[j]), n2); n2 = fmaf(bf_hi(w[j]), bf_hi(w[j]), n2); }
      const uint32_t mx = __reduce_max_sync(0xffffffffu, __float_as_uint(n2) & 0x7FFFFFFFu);
      if (lane == 0) red[sl * 4 + warp] = __uint_as_float(mx);
    }
    bar_sync(1, 256);
    if (tid >= 32 && tid < 44) {
      const int sl = tid - 32, slot = nt * 12 + sl;
      const uint32_t* r = reinterpret_cast<const uint32_t*>(red) + sl * 4;
      if (slot < 64) g_nrm[slot * 16 + rb] = __uint_as_float(max(max(r[0], r[1]), max(r[2], r[3])));
    }
  }
  if (tid == 0) bulk_wait_read();
  TL(1, 7);
  cluster_wait();
}

constexpr int K2_K = 0, K2_V = SLOT_BYTES, K2_Q = 2 * SLOT_BYTES, K2_BAR = K2_Q + 512 * 48, K2_SMEM = K2_BAR + 8 * 19;
constexpr uint32_t EXP_C2 = 0x3EA93EA9u, EXP_C1 = 0x3B4E3B4Eu, EXP_C0 = 0x3F2C3F2Cu;
constexpr int K2_TD = 8 * 384 / 16;

__device__ __forceinline__ void attn_qk(float (&S)[32], const uint32_t (&q)[8], uint64_t kd) {
  wgmma_rs0_n64(S, q[0], q[1], q[2], q[3], kd);
  wgmma_rs_n64(S, q[4], q[5], q[6], q[7], kd + 16, 1);
}
__device__ __forceinline__ void attn_pv(float (&O)[12], const uint32_t (&P)[16], uint64_t vd) {
#pragma unroll
  for (int kk = 0; kk < 4; kk++) wgmma_rs_n24_tb(O, P[4 * kk], P[4 * kk + 1], P[4 * kk + 2], P[4 * kk + 3], vd + kk * 48, 1);
}
__device__ __forceinline__ void attn_exp(float (&S)[32], uint32_t c2, uint32_t cone) {
#pragma unroll
  for (int b = 0; b < 8; b++) {
    if (poly_block(b)) {
#pragma unroll
      for (int h = 0; h < 2; h++) {
        uint32_t w, y;
        asm("prmt.b32 %0, %1, %2, 0x5410;" : "=r"(w) : "r"(__float_as_uint(S[4 * b + 2 * h])), "r"(__float_as_uint(S[4 * b + 2 * h + 1])));
        asm("lop3.b32 %0, %1, 0x007F007F, %2, 0xEA;" : "=r"(y) : "r"(w), "r"(cone));
        const uint32_t p = hfma2(hfma2(y, c2, EXP_C1), y, EXP_C0);
        S[4 * b + 2 * h] = __uint_as_float(w);
        S[4 * b + 2 * h + 1] = __uint_as_float(p);
      }
    } else {
#pragma unroll
      for (int j = 0; j < 4; j++) S[4 * b + j] = ex2(S[4 * b + j]);
    }
  }
}
__device__ __forceinline__ void attn_pack(const float (&S)[32], uint32_t (&P)[16]) {
#pragma unroll
  for (int i = 0; i < 16; i++) {
    if (poly_block(i >> 1)) asm("lop3.b32 %0, %1, %2, 0xFF80FF80, 0xE4;" : "=r"(P[i]) : "r"(__float_as_uint(S[2 * i])), "r"(__float_as_uint(S[2 * i + 1])));
    else P[i] = pack_bf16(S[2 * i], S[2 * i + 1]);
  }
}

__device__ __forceinline__ void attn_load_chunk(uint32_t sb, uint32_t bar, const uint8_t* Kg, int c) {
  mbar_expect(bar + 8 * c, 2 * 6144);
  bulk_g2s(sb + K2_K + c * 6144, Kg + c * 6144, 6144, bar + 8 * c);
  bulk_g2s(sb + K2_V + c * 6144, Kg + (size_t)32 * SLOT_BYTES + c * 6144, 6144, bar + 8 * c);
}

template <bool WAIT>
__device__ __forceinline__ void attn_fast_pass(float (&O)[12], const uint32_t (&q)[8], uint64_t kd, uint64_t vd, uint32_t bar) {
  float S[32]; uint32_t P[16];
  const uint32_t c2 = opaque(EXP_C2), cone = opaque(0x3F803F80u);
  if (WAIT) mbar_wait(bar, 0);
  wg_fence();
  attn_qk(S, q, kd);
  wg_commit();
  wg_wait<0>();
  fence_regs(S);
  attn_exp(S, c2, cone);
  attn_pack(S, P);
  auto step = [&]() {
    kd += K2_TD;
    fence_regs(P); fence_regs(O);
    wg_fence();
    attn_qk(S, q, kd);
    wg_commit();
    attn_pv(O, P, vd);
    wg_commit();
    vd += K2_TD;
    wg_wait<1>();
    fence_regs(S);
    attn_exp(S, c2, cone);
    fence_regs(S);
    wg_wait<0>();
    fence_regs(S); fence_regs(O);
    attn_pack(S, P);
  };
#pragma unroll 1
  for (int c = 1; c < 16; c++) {
    step();
    if (WAIT) mbar_wait(bar + 8 * c, 0);
    step();
  }
  step();
  fence_regs(P); fence_regs(O);
  wg_fence();
  attn_pv(O, P, vd);
  wg_commit();
  wg_wait<0>();
  fence_regs(O);
}

__device__ __forceinline__ void attn_safe_pass(float (&O)[12], const uint32_t (&q)[8], uint64_t kd, uint64_t vd, uint32_t bar) {
  float S[32]; uint32_t P[16];
  float m0 = -INFINITY, m1 = -INFINITY;
#pragma unroll 1
  for (int j = 0; j < 32; j++) {
    if ((j & 1) == 0) mbar_wait(bar + 8 * (j >> 1), 0);
    wg_fence();
    attn_qk(S, q, kd);
    wg_commit();
    wg_wait<0>();
    fence_regs(S);
    float x0 = m0, x1 = m1;
#pragma unroll
    for (int b = 0; b < 8; b++) { x0 = fmaxf(x0, fmaxf(S[4 * b], S[4 * b + 1])); x1 = fmaxf(x1, fmaxf(S[4 * b + 2], S[4 * b + 3])); }
    x0 = fmaxf(x0, __shfl_xor_sync(0xffffffffu, x0, 1)); x0 = fmaxf(x0, __shfl_xor_sync(0xffffffffu, x0, 2));
    x1 = fmaxf(x1, __shfl_xor_sync(0xffffffffu, x1, 1)); x1 = fmaxf(x1, __shfl_xor_sync(0xffffffffu, x1, 2));
    const float a0 = ex2(m0 - x0), a1 = ex2(m1 - x1);
    m0 = x0; m1 = x1;
#pragma unroll
    for (int b = 0; b < 3; b++) { O[4 * b] *= a0; O[4 * b + 1] *= a0; O[4 * b + 2] *= a1; O[4 * b + 3] *= a1; }
#pragma unroll
    for (int b = 0; b < 8; b++) {
      P[2 * b] = pack_bf16(ex2(S[4 * b] - m0), ex2(S[4 * b + 1] - m0));
      P[2 * b + 1] = pack_bf16(ex2(S[4 * b + 2] - m1), ex2(S[4 * b + 3] - m1));
    }
    fence_regs(P); fence_regs(O);
    wg_fence();
    attn_pv(O, P, vd);
    wg_commit();
    wg_wait<0>();
    fence_regs(O);
    kd += K2_TD; vd += K2_TD;
  }
}

__global__ void __launch_bounds__(512, 1) k2_attn(const __grid_constant__ CUtensorMap tm_wmod, const bf16* __restrict__ cvec,
                                                   const bf16* __restrict__ w1, const bf16* __restrict__ w2) {
  extern __shared__ __align__(1024) uint8_t smem[];
  const uint32_t sb = s2u(smem);
  const int head = blockIdx.x >> 2, qg = blockIdx.x & 3;
  const int tid = threadIdx.x, wg = __reduce_max_sync(0xffffffffu, (unsigned)tid >> 7), warp = (tid >> 5) & 3, lane = tid & 31, g = lane >> 2, q4 = lane & 3;
  const uint32_t bar = sb + K2_BAR;
  TL(2, 0);
  if (tid == 0) {
    for (int i = 0; i < 18; i++) mbar_init(bar + 8 * i, 1);
    fence_barrier_init();
  }
  __syncthreads();
  if (blockIdx.x >= 128) {
    mod_tail(cvec, &tm_wmod, blockIdx.x - 128, smem, bar);
    pdl_wait();
    return;
  }
  pdl_wait();
  pdl_launch();
  TL(2, 3);
  if ((tid >> 5) == 1) {
    uint32_t nv = 0;
    if (lane < 16) nv = __float_as_uint(__ldcg(&g_nrm[(32 + head) * 16 + lane]));
    else if (lane < 20) nv = __float_as_uint(__ldcg(&g_nrm[head * 16 + qg * 4 + lane - 16]));
    const uint32_t km = __reduce_max_sync(0xffffffffu, lane < 16 ? nv : 0u), qm = __reduce_max_sync(0xffffffffu, lane < 16 ? 0u : nv);
    if (lane == 0) sts32(bar + 8 * 18, __uint_as_float(km) * __uint_as_float(qm) <= 4096.0f ? 1u : 0u);
  }
  const uint8_t* Kg = g_qkvp + (size_t)(32 + head) * SLOT_BYTES;
  bool fast;
  {
    const uint8_t* Qg = g_qkvp + (size_t)head * SLOT_BYTES + (size_t)qg * 512 * 48;
    if (tid == 0) {
      mbar_expect(bar + 8 * 16, 4 * 3072);
      for (int w = 0; w < 4; w++) bulk_g2s(sb + K2_Q + w * 6144, Qg + w * 6144, 3072, bar + 8 * 16);
      for (int c = 0; c < 2; c++) attn_load_chunk(sb, bar, Kg, c);
    }
    __syncthreads();
    fast = lds32(bar + 8 * 18) != 0;
    if (tid == 32) {
      for (int c = 2; c < 16; c++) attn_load_chunk(sb, bar, Kg, c);
      mbar_expect(bar + 8 * 17, 4 * 3072);
      for (int w = 0; w < 4; w++) bulk_g2s(sb + K2_Q + w * 6144 + 3072, Qg + w * 6144 + 3072, 3072, bar + 8 * 17);
    }
    __syncwarp();
  }
  TL(2, 1);
  const uint64_t kd = mkdesc(sb + K2_K, 128, 384, 0);
  const uint64_t vd = mkdesc(sb + K2_V, 384, 128, 0);
#pragma unroll 1
  for (int it = 0; it < 2; it++) {
    const int qt = wg * 2 + it;
    mbar_wait(bar + 8 * (16 + it), 0);
    if (it == 0) TL(2, 4);
    uint32_t q[8];
    {
      const uint32_t base = sb + K2_Q + (qt * 8 + warp * 2) * 384 + g * 16 + q4 * 4;
#pragma unroll
      for (int j = 0; j < 3; j++) { q[2 * j] = lds32(base + j * 128); q[2 * j + 1] = lds32(base + 384 + j * 128); }
      if (fast && q4 == 1) { q[4] = 0x3F803F80u; q[5] = 0x3F803F80u; }
      q[6] = opaque(0u); q[7] = opaque(0u);
    }
    if (it == 1 && tid == 0) {
      const char* a = reinterpret_cast<const char*>(w1) + (size_t)blockIdx.x * (DM * FF * 2 / 128);
      const char* b = reinterpret_cast<const char*>(w2) + (size_t)blockIdx.x * (DM * FF * 2 / 128);
      asm volatile("cp.async.bulk.prefetch.L2.global [%0], %1;" :: "l"(a), "r"(DM * FF * 2 / 128) : "memory");
      asm volatile("cp.async.bulk.prefetch.L2.global [%0], %1;" :: "l"(b), "r"(DM * FF * 2 / 128) : "memory");
    }
    float O[12];
#pragma unroll
    for (int i = 0; i < 12; i++) O[i] = 0.f;
    if (fast) {
      if (it == 0) attn_fast_pass<true>(O, q, kd, vd, bar);
      else attn_fast_pass<false>(O, q, kd, vd, bar);
    } else {
      attn_safe_pass(O, q, kd, vd, bar);
    }
    const float l0 = __shfl_sync(0xffffffffu, O[8], (lane & ~3) | 1), l1 = __shfl_sync(0xffffffffu, O[10], (lane & ~3) | 1);
    const float r0 = __frcp_rn(l0), r1 = __frcp_rn(l1);
    const int row = qg * 512 + qt * 64 + warp * 16 + g;
    uint32_t* o0 = reinterpret_cast<uint32_t*>(g_o + (size_t)row * DM + head * DHEAD + q4 * 2);
    uint32_t* o1 = o0 + 8 * DM / 2;
    o0[0] = pack_bf16(O[0] * r0, O[1] * r0);  o1[0] = pack_bf16(O[2] * r1, O[3] * r1);
    o0[4] = pack_bf16(O[4] * r0, O[5] * r0);  o1[4] = pack_bf16(O[6] * r1, O[7] * r1);
    if (q4 == 0) { o0[8] = pack_bf16(O[8] * r0, O[9] * r0);  o1[8] = pack_bf16(O[10] * r1, O[11] * r1); }
  }
  TL(2, 7);
}

constexpr int K3_A = 0, K3_W = 147456, K3_X = K3_W, K3_MOD = K3_W + 9 * 9216, K3_BAR = K3_MOD + 3 * 144 + 16;
constexpr int K3_SMEM = K3_BAR + 8 * (9 + 9 + 3);

__global__ void __launch_bounds__(320, 1) k3_wo(const __grid_constant__ CUtensorMap tm_o, const __grid_constant__ CUtensorMap tm_wo,
                                                const __grid_constant__ CUtensorMap tm_x, const __grid_constant__ CUtensorMap tm_x2,
                                                const __grid_constant__ CUtensorMap tm_h2) {
  extern __shared__ __align__(1024) uint8_t smem[];
  const uint32_t sb = s2u(smem);
  const int tid = threadIdx.x, nt = blockIdx.x & 7, rb = blockIdx.x >> 3;
  const uint32_t bw = sb + K3_BAR, baf = bw + 72, bxb = baf + 72, bmd = bxb + 8, bxe = bmd + 8;
  TL(3, 0);
  if (tid == 256) {
    for (int i = 0; i < 20; i++) mbar_init(bw + 8 * i, 1);
    mbar_init(bxe, 2);
    fence_barrier_init();
    tmap_prefetch(&tm_o); tmap_prefetch(&tm_wo); tmap_prefetch(&tm_x); tmap_prefetch(&tm_x2); tmap_prefetch(&tm_h2);
  }
  __syncthreads();
  cluster_arrive_relaxed();
  pdl_launch();
  if (tid >= 288) {
    if (tid == 288)
      for (int c = 0; c < 9; c++) { mbar_expect(bw + 8 * c, 9216); tma2d(sb + K3_W + c * 9216, &tm_wo, c * 64, nt * 72, bw + 8 * c); }
    __syncwarp();
    cluster_wait();
    return;
  }
  if (tid >= 256) {
    cluster_wait();
    if (tid == 256) {
      const int rank = cluster_rank();
      pdl_wait();
      for (int c = 0; c < 9; c++) {
        mbar_expect(baf + 8 * c, 16384);
        tma2d_mc(sb + K3_A + c * 16384 + rank * 8192, &tm_o, c * 64, rb * 128 + rank * 64, baf + 8 * c);
      }
      mbar_expect(bmd, 3 * 144);
      for (int v = 0; v < 3; v++) bulk_g2s(sb + K3_MOD + v * 144, g_mod + (2 + v) * DM + nt * 72, 144, bmd);
      mbar_wait(bxe, 0);
      mbar_expect(bxb, 18432); tma2d(sb + K3_X, &tm_x, nt * 72, rb * 128, bxb);
    }
    __syncwarp();
    cluster_arrive_relaxed(); cluster_wait();
    return;
  }
  const int wg = __reduce_max_sync(0xffffffffu, (unsigned)tid >> 7), wtid = tid & 127, warp = (tid >> 5) & 3, lane = tid & 31, g = lane >> 2, q4 = lane & 3;
  const int lrow = wg * 64 + warp * 16 + g;
  cluster_wait();
  pdl_wait();
  TL(3, 1);
  const uint32_t tag = __ldcg(&g_epoch);
  float acc[36];
#pragma unroll
  for (int i = 0; i < 36; i++) acc[i] = 0.f;
  const uint64_t da0 = mkdesc(sb + K3_A + wg * 8192, 16, 1024, 1);
  const uint64_t db0 = mkdesc(sb + K3_W, 16, 1024, 1);
#pragma unroll 1
  for (int c = 0; c < 9; c++) {
    mbar_wait(bw + 8 * c, 0);
    mbar_wait(baf + 8 * c, 0);
    wg_fence();
#pragma unroll
    for (int j = 0; j < 4; j++) wgmma_ss_n72(acc, da0 + (uint64_t)(c * 1024 + j * 2), db0 + (uint64_t)(c * 576 + j * 2), 1);
    wg_commit();
    if (c == 2) { wg_wait<1>(); if (wtid == 0) mbar_arrive(bxe); }
  }
  wg_wait<0>();
  fence_regs(acc);
  cluster_arrive_relaxed();
  TL(3, 2);
  mbar_wait(bmd, 0);
  mbar_wait(bxb, 0);
  const uint32_t xa = sb + K3_X + lrow * 144 + q4 * 4, ma = sb + K3_MOD + q4 * 4;
  float s0 = 0.f, s1 = 0.f;
#pragma unroll
  for (int i = 0; i < 9; i++) {
    const uint32_t x0 = lds32(xa + 16 * i), x1 = lds32(xa + 8 * 144 + 16 * i), ga = lds32(ma + 16 * i);
    const float g0 = bf_lo(ga), g1 = bf_hi(ga);
    const uint32_t p0 = pack_bf16(fmaf(g0, acc[4 * i], bf_lo(x0)), fmaf(g1, acc[4 * i + 1], bf_hi(x0)));
    const uint32_t p1 = pack_bf16(fmaf(g0, acc[4 * i + 2], bf_lo(x1)), fmaf(g1, acc[4 * i + 3], bf_hi(x1)));
    sts32(xa + 16 * i, p0); sts32(xa + 8 * 144 + 16 * i, p1);
    acc[4 * i] = bf_lo(p0); acc[4 * i + 1] = bf_hi(p0); acc[4 * i + 2] = bf_lo(p1); acc[4 * i + 3] = bf_hi(p1);
    s0 += acc[4 * i] + acc[4 * i + 1]; s1 += acc[4 * i + 2] + acc[4 * i + 3];
  }
  s0 += __shfl_xor_sync(0xffffffffu, s0, 1); s1 += __shfl_xor_sync(0xffffffffu, s1, 1);
  s0 += __shfl_xor_sync(0xffffffffu, s0, 2); s1 += __shfl_xor_sync(0xffffffffu, s1, 2);
  const float m0 = s0 * (1.0f / 72), m1 = s1 * (1.0f / 72);
  float v0 = 0.f, v1 = 0.f;
#pragma unroll
  for (int i = 0; i < 9; i++) {
    float d;
    d = acc[4 * i] - m0; v0 = fmaf(d, d, v0); d = acc[4 * i + 1] - m0; v0 = fmaf(d, d, v0);
    d = acc[4 * i + 2] - m1; v1 = fmaf(d, d, v1); d = acc[4 * i + 3] - m1; v1 = fmaf(d, d, v1);
  }
  v0 += __shfl_xor_sync(0xffffffffu, v0, 1); v1 += __shfl_xor_sync(0xffffffffu, v1, 1);
  v0 += __shfl_xor_sync(0xffffffffu, v0, 2); v1 += __shfl_xor_sync(0xffffffffu, v1, 2);
  if (q4 < 2) {
    const float mm = q4 ? m1 : m0, vv = q4 ? v1 : v0;
    asm volatile("st.relaxed.gpu.global.v2.b64 [%0], {%1, %2};"
                 :: "l"(&g_stats[(rb * 8 + nt) * 128 + lrow + 8 * q4]), "l"(((uint64_t)tag << 32) | __float_as_uint(mm)), "l"(((uint64_t)tag << 32) | __float_as_uint(vv)) : "memory");
  }
  fence_async_smem();
  bar_sync(1, 256);
  TL(3, 3);
  if (tid == 0) { tma2d_store(&tm_x2, sb + K3_X, nt * 72, rb * 128); bulk_commit(); }
  float mean0, mean1, rs0, rs1;
  {
    uint64_t w[8];
    const uint4* pa = &g_stats[(rb * 8 + 2 * q4) * 128 + lrow];
    for (int it = 0; it < (1 << 20); it++) {
      asm volatile("ld.relaxed.gpu.global.v2.b64 {%0, %1}, [%2];" : "=l"(w[0]), "=l"(w[1]) : "l"(pa) : "memory");
      asm volatile("ld.relaxed.gpu.global.v2.b64 {%0, %1}, [%2];" : "=l"(w[2]), "=l"(w[3]) : "l"(pa + 128) : "memory");
      asm volatile("ld.relaxed.gpu.global.v2.b64 {%0, %1}, [%2];" : "=l"(w[4]), "=l"(w[5]) : "l"(pa + 8) : "memory");
      asm volatile("ld.relaxed.gpu.global.v2.b64 {%0, %1}, [%2];" : "=l"(w[6]), "=l"(w[7]) : "l"(pa + 136) : "memory");
      bool ok = true;
#pragma unroll
      for (int j = 0; j < 8; j++) ok = ok && (uint32_t)(w[j] >> 32) == tag;
      if (__all_sync(0xffffffffu, ok)) break;
      __nanosleep(200);
    }
    const float ax = __uint_as_float((uint32_t)w[0]), ay = __uint_as_float((uint32_t)w[1]), az = __uint_as_float((uint32_t)w[2]), aw = __uint_as_float((uint32_t)w[3]);
    const float bx = __uint_as_float((uint32_t)w[4]), by = __uint_as_float((uint32_t)w[5]), bz = __uint_as_float((uint32_t)w[6]), bw_ = __uint_as_float((uint32_t)w[7]);
    float sa = ax + az, sb_ = bx + bz;
    sa += __shfl_xor_sync(0xffffffffu, sa, 1); sb_ += __shfl_xor_sync(0xffffffffu, sb_, 1);
    sa += __shfl_xor_sync(0xffffffffu, sa, 2); sb_ += __shfl_xor_sync(0xffffffffu, sb_, 2);
    mean0 = sa * 0.125f; mean1 = sb_ * 0.125f;
    float ma2 = ay + aw + 72.f * ((ax - mean0) * (ax - mean0) + (az - mean0) * (az - mean0));
    float mb2 = by + bw_ + 72.f * ((bx - mean1) * (bx - mean1) + (bz - mean1) * (bz - mean1));
    ma2 += __shfl_xor_sync(0xffffffffu, ma2, 1); mb2 += __shfl_xor_sync(0xffffffffu, mb2, 1);
    ma2 += __shfl_xor_sync(0xffffffffu, ma2, 2); mb2 += __shfl_xor_sync(0xffffffffu, mb2, 2);
    rs0 = rsqrtf(ma2 * (1.0f / DM) + 1e-5f); rs1 = rsqrtf(mb2 * (1.0f / DM) + 1e-5f);
  }
  TL(3, 4);
  {
    const uint32_t ha = sb + K3_A + lrow * 144 + q4 * 4;
#pragma unroll
    for (int i = 0; i < 9; i++) {
      const uint32_t c1p = hadd2(lds32(ma + 288 + 16 * i), 0x3F803F80u), sh = lds32(ma + 144 + 16 * i);
      sts32(ha + 16 * i, hfma2(hfma2(pack_bf16((acc[4 * i] - mean0) * rs0, (acc[4 * i + 1] - mean0) * rs0), c1p, sh), 0x3F003F00u, 0x80008000u));
      sts32(ha + 8 * 144 + 16 * i, hfma2(hfma2(pack_bf16((acc[4 * i + 2] - mean1) * rs1, (acc[4 * i + 3] - mean1) * rs1), c1p, sh), 0x3F003F00u, 0x80008000u));
    }
  }
  fence_async_smem();
  bar_sync(1, 256);
  if (tid == 0) { tma2d_store(&tm_h2, sb + K3_A, nt * 72, rb * 128); bulk_commit(); bulk_wait_read(); }
  TL(3, 7);
  cluster_wait();
}

constexpr int K4_BK = 64;
constexpr int K4_KS = K4_BK / 16;
constexpr int K4_SPT = 576 / K4_BK;
constexpr int K4_NST = 3 * 64 / K4_BK;
constexpr int K4_STB = K4_BK * 384;
constexpr int K4_A = 0, K4_B = 147456, K4_BAR = K4_B + K4_NST * K4_STB, K4_SMEM = K4_BAR + 8 * (9 + 2 * K4_NST) + 8;

__device__ __forceinline__ uint32_t silu2(uint32_t v, uint32_t m16, uint32_t mhi) {
  const float lo = __uint_as_float(v * m16), hi = __uint_as_float(v & mhi);
  return pack_bf16(fmaf(lo, tanh_fast(lo), lo), fmaf(hi, tanh_fast(hi), hi));
}
template <int P>
__device__ __forceinline__ void k4_epi(const uint32_t (&pk)[48], uint32_t go, bf16* hp) {
  const uint32_t m16 = go << 16, mhi = 0u - m16;
  constexpr int B = 8 * (P >> 1) + (P & 1);
  uint4 r;
  r.x = silu2(pk[B], m16, mhi); r.y = silu2(pk[B + 2], m16, mhi); r.z = silu2(pk[B + 4], m16, mhi); r.w = silu2(pk[B + 6], m16, mhi);
  asm volatile("st.global.v4.b32 [%0], {%1,%2,%3,%4};" :: "l"(hp + (P & 1) * 8 * FF + 32 * (P >> 1)), "r"(r.x), "r"(r.y), "r"(r.z), "r"(r.w) : "memory");
}
template <int P0, int N>
__device__ __forceinline__ void k4_epi_n(const uint32_t (&pk)[48], uint32_t go, bf16* hp) {
  if constexpr (N > 0) { k4_epi<P0>(pk, go, hp); k4_epi_n<P0 + 1, N - 1>(pk, go, hp); }
}
__host__ __device__ constexpr int k4_first(int i) { return (i * 12 + 8) / 9; }

template <int T, int I>
__device__ __forceinline__ void k4_steps(float (&acc)[96], const uint32_t (&pk)[48], uint64_t da0, uint64_t db0, uint32_t ba, uint32_t bbf,
                                         uint32_t rbe, int wtid, bf16* hp) {
  if constexpr (I < K4_SPT) {
    constexpr int st = T * K4_SPT + I, s = st % K4_NST, k0 = I * K4_KS;
    if (T == 0 && (k0 & 3) == 0) mbar_wait(ba + 8 * (k0 >> 2), 0);
    mbar_wait(bbf + 8 * s, (st / K4_NST) & 1);
    wg_fence();
#pragma unroll
    for (int j = 0; j < K4_KS; j++)
      wgmma_ss_n192_tb(acc, da0 + (uint64_t)(((k0 + j) >> 2) * 1024 + ((k0 + j) & 3) * 2), db0 + (uint64_t)(s * (K4_STB / 16) + j * 128), (I | j) != 0);
    wg_commit();
    if constexpr (I > 0) {
      wg_wait<1>();
      if (st - 1 + K4_NST < 3 * K4_SPT && wtid < 2) mbar_arrive_remote(rbe + 8 * ((st - 1) % K4_NST));
    }
    if constexpr (T > 0 && k4_first(I + 1) > k4_first(I)) {
      const uint32_t go = mbar_try(ba, 0);
      k4_epi_n<k4_first(I), k4_first(I + 1) - k4_first(I)>(pk, go, hp);
    }
    k4_steps<T, I + 1>(acc, pk, da0, db0, ba, bbf, rbe, wtid, hp);
  }
}
template <int T>
__device__ __forceinline__ void k4_tile(float (&acc)[96], const uint32_t (&pk)[48], uint64_t da0, uint64_t db0, uint32_t ba, uint32_t bbf,
                                        uint32_t rbe, int wtid, bf16* hprev) {
  k4_steps<T, 0>(acc, pk, da0, db0, ba, bbf, rbe, wtid, hprev);
  wg_wait<0>();
  fence_regs(acc);
  if (T * K4_SPT + K4_SPT - 1 + K4_NST < 3 * K4_SPT && wtid < 2) mbar_arrive_remote(rbe + 8 * ((T * K4_SPT + K4_SPT - 1) % K4_NST));
}
__device__ __forceinline__ void k4_pack(const float (&acc)[96], uint32_t (&pk)[48]) {
#pragma unroll
  for (int i = 0; i < 48; i++) pk[i] = pack_bf16(acc[2 * i], acc[2 * i + 1]);
}

__global__ void __launch_bounds__(384, 1) k4_mlp1(const __grid_constant__ CUtensorMap tm_h2, const __grid_constant__ CUtensorMap tm_w1) {
  extern __shared__ __align__(1024) uint8_t smem[];
  const uint32_t sb = s2u(smem);
  const int tid = threadIdx.x, rb = blockIdx.x & 15, fs = blockIdx.x >> 4;
  const uint32_t ba = sb + K4_BAR, bbf = ba + 72, bbe = bbf + 8 * K4_NST;
  TL(4, 0);
  if (tid == 0) {
    for (int i = 0; i < 9; i++) mbar_init(ba + 8 * i, 1);
    for (int i = 0; i < K4_NST; i++) { mbar_init(bbf + 8 * i, 1); mbar_init(bbe + 8 * i, 4); }
    fence_barrier_init();
    tmap_prefetch(&tm_h2); tmap_prefetch(&tm_w1);
  }
  __syncthreads();
  cluster_arrive_relaxed();
  pdl_launch();
  if (tid < 128) {
    reg_dec<40>();
    if (tid >= 32 && tid < 64) {
      auto load_a = [&](int c) { mbar_expect(ba + 8 * c, 16384); tma2d(sb + K4_A + c * 16384, &tm_h2, c * 64, rb * 128, ba + 8 * c); };
      if (tid == 32) {
        pdl_wait();
        for (int c = 0; c < 4; c++) load_a(c);
      }
      __syncwarp();
      cluster_wait();
      if (tid == 32)
        for (int c = 4; c < 9; c++) { mbar_wait(ba + 8 * (c - 4), 0); load_a(c); }
    } else {
      cluster_wait();
      if (tid == 0) {
        const int rank = cluster_rank();
        for (int st = 0; st < 3 * K4_SPT; st++) {
          const int s = st % K4_NST, t = st / K4_SPT, i = st % K4_SPT;
          if (st >= K4_NST) mbar_wait(bbe + 8 * s, (st / K4_NST - 1) & 1);
          mbar_expect(bbf + 8 * s, K4_STB);
          for (int g = 0; g < 3; g++)
            tma2d_mc(sb + K4_B + s * K4_STB + g * (K4_STB / 3) + rank * (K4_STB / 6), &tm_w1, fs * 576 + t * 192 + g * 64, i * K4_BK + rank * (K4_BK / 2), bbf + 8 * s);
        }
        cluster_arrive_relaxed(); cluster_wait();
      }
    }
  } else {
    reg_inc<232>();
    const int wg = __reduce_max_sync(0xffffffffu, ((unsigned)tid >> 7) - 1), wtid = tid & 127, warp = (tid >> 5) & 3, lane = tid & 31;
    const uint64_t da0 = mkdesc(sb + K4_A + wg * 8192, 16, 1024, 1);
    const uint64_t db0 = mkdesc(sb + K4_B, K4_STB / 3, 1024, 1);
    cluster_wait();
    const uint32_t rbe = map_cta(bbe, wtid & 1);
    bf16* hp = g_H + (size_t)(rb * 128 + wg * 64 + warp * 16 + (lane >> 2)) * FF + fs * 576 + (lane & 3) * 8;
    float acc[96]; uint32_t pk[48];
#pragma unroll
    for (int i = 0; i < 96; i++) acc[i] = 0.f;
    TLT(4, 1, 128); TLC(4, 3, 128);
    k4_tile<0>(acc, pk, da0, db0, ba, bbf, rbe, wtid, hp);
    k4_pack(acc, pk);
    k4_tile<1>(acc, pk, da0, db0, ba, bbf, rbe, wtid, hp);
    k4_pack(acc, pk);
    k4_tile<2>(acc, pk, da0, db0, ba, bbf, rbe, wtid, hp + 192);
    cluster_arrive_relaxed();
    TLT(4, 2, 128); TLC(4, 4, 128);
    k4_pack(acc, pk);
    k4_epi_n<0, 12>(pk, 1u, hp + 384);
    TLT(4, 7, 128);
    cluster_wait();
  }
}

constexpr int K5_NST = 4;
constexpr int K5_STAGE = 16384 + 36864;
constexpr int K5_GB = K5_NST * K5_STAGE, K5_BAR = K5_GB + 576, K5_SMEM = K5_BAR + 8 * (2 * K5_NST + 1);

template <int I> __device__ __forceinline__ float k5_acc(const float (&a)[128], const float (&b)[16]) { if constexpr (I < 128) return a[I]; else return b[I - 128]; }

template <int QD, int I>
__device__ __forceinline__ void k5_stage(const float (&a)[128], const float (&b)[16], uint32_t dst, uint32_t gbs) {
  if constexpr (I < 9) {
    constexpr int B = 9 * QD + I;
    const uint32_t gb = lds32(gbs + B * 16);
    const float g0 = bf_lo(gb), g1 = bf_hi(gb);
    sts32(dst + I * 16, pack_bf16(k5_acc<4 * B>(a, b) * g0, k5_acc<4 * B + 1>(a, b) * g1));
    sts32(dst + 8 * 144 + I * 16, pack_bf16(k5_acc<4 * B + 2>(a, b) * g0, k5_acc<4 * B + 3>(a, b) * g1));
    k5_stage<QD, I + 1>(a, b, dst, gbs);
  }
}
template <int QD>
__device__ __forceinline__ void k5_quarter(const float (&a)[128], const float (&b)[16], uint32_t sb, uint32_t dst, uint32_t gbs, int wg, int wtid,
                                           const CUtensorMap* tm, int col, int row) {
  k5_stage<QD, 0>(a, b, dst + QD * 18432, gbs);
  fence_async_smem();
  bar_sync(2 + wg, 128);
  if (wtid == 0) {
    asm volatile("cp.reduce.async.bulk.tensor.2d.global.shared::cta.add.tile.bulk_group [%0, {%2, %3}], [%1];"
                 :: "l"(tm), "r"(sb + QD * 18432 + wg * 9216), "r"(col + QD * 72), "r"(row) : "memory");
    bulk_commit();
  }
}

__global__ void __launch_bounds__(384, 1) k5_mlp2(const __grid_constant__ CUtensorMap tm_h, const __grid_constant__ CUtensorMap tm_w2,
                                                  const __grid_constant__ CUtensorMap tm_w2n, const __grid_constant__ CUtensorMap tm_out) {
  extern __shared__ __align__(1024) uint8_t smem[];
  const uint32_t sb = s2u(smem);
  const int tid = threadIdx.x, rb = blockIdx.x & 15, nh = (blockIdx.x >> 4) & 1, ks = blockIdx.x >> 5;
  const uint32_t bf = sb + K5_BAR, be = bf + 8 * K5_NST, bg = be + 8 * K5_NST;
  TL(5, 0);
  if (tid == 0) {
    for (int i = 0; i < K5_NST; i++) { mbar_init(bf + 8 * i, 1); mbar_init(be + 8 * i, 4); }
    mbar_init(bg, 1);
    fence_barrier_init();
    tmap_prefetch(&tm_h); tmap_prefetch(&tm_w2); tmap_prefetch(&tm_w2n); tmap_prefetch(&tm_out);
  }
  __syncthreads();
  cluster_arrive_relaxed(); cluster_wait();
  const int rank = cluster_rank();
  if (tid < 128) {
    reg_dec<40>();
    if (tid == 0) {
      auto load_b = [&](int st) {
        const int s = st % K5_NST;
        mbar_expect(bf + 8 * s, K5_STAGE);
        for (int g = 2 * rank; g < 2 * rank + 2; g++)
          tma5d_mc(sb + s * K5_STAGE + 16384 + g * 8192, &tm_w2, nh * 288 + g * 64, 0, 0, 0, (ks * 18 + st) * 2, bf + 8 * s);
        if (rank == 1) tma5d_mc(sb + s * K5_STAGE + 16384 + 32768, &tm_w2n, nh * 288 + 256, 0, 0, 0, (ks * 18 + st) * 2, bf + 8 * s);
      };
      load_b(0);
      pdl_wait();
      for (int st = 0; st < 18; st++) {
        const int s = st % K5_NST;
        if (st >= K5_NST) mbar_wait(be + 8 * s, (st / K5_NST - 1) & 1);
        if (st >= 1) load_b(st);
        tma2d(sb + s * K5_STAGE, &tm_h, (ks * 18 + st) * 64, rb * 128, bf + 8 * s);
        if (st == K5_NST) { mbar_expect(bg, 576); bulk_g2s(sb + K5_GB, g_mod + 5 * DM + nh * 288, 576, bg); }
      }
      cluster_arrive_relaxed(); cluster_wait();
    }
  } else {
    reg_inc<232>();
    const int ctid = tid - 128, wg = __reduce_max_sync(0xffffffffu, (unsigned)ctid >> 7), wtid = tid & 127, warp = (tid >> 5) & 3, lane = tid & 31, g = lane >> 2, q4 = lane & 3;
    float a[128], b[16];
#pragma unroll
    for (int i = 0; i < 128; i++) a[i] = 0.f;
#pragma unroll
    for (int i = 0; i < 16; i++) b[i] = 0.f;
    const uint64_t db0 = mkdesc(sb + 16384, 8192, 1024, 1);
    const uint64_t dn0 = mkdesc(sb + 16384 + 32768, 4096, 512, 2);
    const uint32_t rbe = map_cta(be, wtid & 1);
    uint32_t aoff[4];
    {
      const int r = wg * 64 + warp * 16 + (lane & 7) + ((lane >> 3) & 1) * 8;
#pragma unroll
      for (int j = 0; j < 4; j++) aoff[j] = sb + r * 128 + (((2 * j + (lane >> 4)) ^ (lane & 7)) << 4);
    }
    uint32_t A0[4][4], A1[4][4];
    auto step = [&](uint32_t (&A)[4][4], int st) {
      const int s = st % K5_NST;
      mbar_wait(bf + 8 * s, (st / K5_NST) & 1);
#pragma unroll
      for (int j = 0; j < 4; j++) ldsm4(A[j], aoff[j] + s * K5_STAGE);
      fence_regs(A[0]); fence_regs(A[1]); fence_regs(A[2]); fence_regs(A[3]);
      wg_fence();
#pragma unroll
      for (int j = 0; j < 4; j++) {
        wgmma_rs_n256_tb(a, A[j][0], A[j][1], A[j][2], A[j][3], db0 + (uint64_t)(s * (K5_STAGE / 16) + j * 128), 1);
        wgmma_rs_n32_tb(b, A[j][0], A[j][1], A[j][2], A[j][3], dn0 + (uint64_t)(s * (K5_STAGE / 16) + j * 64), 1);
      }
      wg_commit();
      if (st > 0) {
        wg_wait<1>();
        if (st - 1 + K5_NST < 18 && wtid < 2) mbar_arrive_remote(rbe + 8 * ((st - 1) % K5_NST));
      }
    };
#pragma unroll 1
    for (int st = 0; st < 18; st += 2) { step(A0, st); step(A1, st + 1); }
    wg_wait<0>();
    fence_regs(a); fence_regs(b);
    cluster_arrive_relaxed();
    TLT(5, 2, 128);
    mbar_wait(bg, 0);
    bar_sync(1, 256);
    const uint32_t dst = sb + (wg * 64 + warp * 16 + g) * 144 + q4 * 4, gbs = sb + K5_GB + q4 * 4;
    k5_quarter<0>(a, b, sb, dst, gbs, wg, wtid, &tm_out, nh * 288, rb * 128 + wg * 64);
    k5_quarter<1>(a, b, sb, dst, gbs, wg, wtid, &tm_out, nh * 288, rb * 128 + wg * 64);
    k5_quarter<2>(a, b, sb, dst, gbs, wg, wtid, &tm_out, nh * 288, rb * 128 + wg * 64);
    k5_quarter<3>(a, b, sb, dst, gbs, wg, wtid, &tm_out, nh * 288, rb * 128 + wg * 64);
    TLT(5, 3, 128);
    if (wtid == 0) bulk_wait_read();
    TLT(5, 7, 128);
    cluster_wait();
  }
}

}

typedef CUresult (*EncodeTiledFn)(CUtensorMap*, CUtensorMapDataType, cuuint32_t, void*, const cuuint64_t*, const cuuint64_t*, const cuuint32_t*,
                                  const cuuint32_t*, CUtensorMapInterleave, CUtensorMapSwizzle, CUtensorMapL2promotion, CUtensorMapFloatOOBfill);

static void make_map2d(EncodeTiledFn enc, CUtensorMap* m, const void* base, int cols, int rows, int box_cols, int box_rows, CUtensorMapSwizzle sw) {
  cuuint64_t dims[2] = {(cuuint64_t)cols, (cuuint64_t)rows};
  cuuint64_t strides[1] = {(cuuint64_t)cols * 2};
  cuuint32_t box[2] = {(cuuint32_t)box_cols, (cuuint32_t)box_rows};
  cuuint32_t es[2] = {1, 1};
  enc(m, CU_TENSOR_MAP_DATA_TYPE_BFLOAT16, 2, const_cast<void*>(base), dims, strides, box, es, CU_TENSOR_MAP_INTERLEAVE_NONE, sw,
      CU_TENSOR_MAP_L2_PROMOTION_L2_128B, CU_TENSOR_MAP_FLOAT_OOB_FILL_NONE);
}

template <typename... KArgs, typename... Args>
static void launch(void (*kern)(KArgs...), int grid, int block, int smem, bool pdl, int cluster, Args... args) {
  cudaLaunchConfig_t cfg = {};
  cfg.gridDim = dim3(grid); cfg.blockDim = dim3(block); cfg.dynamicSmemBytes = smem; cfg.stream = cudaStreamPerThread;
  cudaLaunchAttribute at[2];
  int n = 0;
  if (pdl) { at[n].id = cudaLaunchAttributeProgrammaticStreamSerialization; at[n].val.programmaticStreamSerializationAllowed = 1; n++; }
  if (cluster > 1) { at[n].id = cudaLaunchAttributeClusterDimension; at[n].val.clusterDim.x = cluster; at[n].val.clusterDim.y = 1; at[n].val.clusterDim.z = 1; n++; }
  cfg.attrs = at; cfg.numAttrs = n;
  cudaLaunchKernelEx(&cfg, kern, KArgs(args)...);
}

#define USE_PDL 1

extern "C" void kernel_launch(void* const* d_in, const int* in_sizes, int n_in, void* d_out, int out_size) {
  (void)in_sizes; (void)n_in; (void)out_size;
  const bf16* x    = (const bf16*)d_in[0];
  const bf16* wqkv = (const bf16*)d_in[1];
  const bf16* wo   = (const bf16*)d_in[2];
  const bf16* w1   = (const bf16*)d_in[4];
  const bf16* w2   = (const bf16*)d_in[5];
  const bf16* c    = (const bf16*)d_in[6];
  const bf16* wmod = (const bf16*)d_in[7];
  bf16* out = (bf16*)d_out;

  static EncodeTiledFn enc = nullptr;
  if (!enc) {
    void* fn = nullptr; cudaDriverEntryPointQueryResult qr;
    cudaGetDriverEntryPoint("cuTensorMapEncodeTiled", &fn, cudaEnableDefault, &qr);
    enc = (EncodeTiledFn)fn;
    cudaFuncSetAttribute(k1_qkv, cudaFuncAttributeMaxDynamicSharedMemorySize, K1_SMEM);
    cudaFuncSetAttribute(k2_attn, cudaFuncAttributeMaxDynamicSharedMemorySize, K2_SMEM);
    cudaFuncSetAttribute(k3_wo, cudaFuncAttributeMaxDynamicSharedMemorySize, K3_SMEM);
    cudaFuncSetAttribute(k4_mlp1, cudaFuncAttributeMaxDynamicSharedMemorySize, K4_SMEM);
    cudaFuncSetAttribute(k5_mlp2, cudaFuncAttributeMaxDynamicSharedMemorySize, K5_SMEM);
  }
  void *p_arena, *p_woT;
  cudaGetSymbolAddress(&p_arena, g_arena); cudaGetSymbolAddress(&p_woT, g_woT);
  void* p_h2 = p_arena;
  void* p_xn = (uint8_t*)p_arena + 96 * SLOT_BYTES;
  void* p_o = p_xn;
  void* p_H = (uint8_t*)p_arena + ACT_BYTES;
  CUtensorMap tm_xn, tm_wqkv, tm_o, tm_wo, tm_x, tm_x2s, tm_h2s, tm_h2, tm_w1, tm_H, tm_w2, tm_w2n, tm_out, tm_wmod;
  make_map2d(enc, &tm_xn, p_xn, DM, SEQ, 64, 128, CU_TENSOR_MAP_SWIZZLE_128B);
  make_map2d(enc, &tm_wqkv, wqkv, 3 * DM, DM, 64, 32, CU_TENSOR_MAP_SWIZZLE_128B);
  make_map2d(enc, &tm_o, p_o, DM, SEQ, 64, 64, CU_TENSOR_MAP_SWIZZLE_128B);
  make_map2d(enc, &tm_x, x, DM, SEQ, 72, 128, CU_TENSOR_MAP_SWIZZLE_NONE);
  make_map2d(enc, &tm_wmod, wmod, 6 * DM, DM, 192, 64, CU_TENSOR_MAP_SWIZZLE_NONE);
  make_map2d(enc, &tm_x2s, out, DM, SEQ, 72, 128, CU_TENSOR_MAP_SWIZZLE_NONE);
  make_map2d(enc, &tm_out, out, DM, SEQ, 72, 64, CU_TENSOR_MAP_SWIZZLE_NONE);
  make_map2d(enc, &tm_h2s, p_h2, DM, SEQ, 72, 128, CU_TENSOR_MAP_SWIZZLE_NONE);
  make_map2d(enc, &tm_wo, p_woT, DM, DM, 64, 72, CU_TENSOR_MAP_SWIZZLE_128B);
  make_map2d(enc, &tm_h2, p_h2, DM, SEQ, 64, 128, CU_TENSOR_MAP_SWIZZLE_128B);
  make_map2d(enc, &tm_w1, w1, FF, DM, 64, K4_BK / 2, CU_TENSOR_MAP_SWIZZLE_128B);
  make_map2d(enc, &tm_H, p_H, FF, SEQ, 64, 128, CU_TENSOR_MAP_SWIZZLE_128B);
  for (int narrow = 0; narrow < 2; narrow++) {
    cuuint64_t dims[5] = {(cuuint64_t)DM, 2, 4, 4, (cuuint64_t)(FF / 32)};
    cuuint64_t strides[4] = {(cuuint64_t)DM * 2, (cuuint64_t)DM * 2 * 8, (cuuint64_t)DM * 2 * 2, (cuuint64_t)DM * 2 * 32};
    cuuint32_t box[5] = {narrow ? 32u : 64u, 2, 4, 4, 2};
    cuuint32_t es[5] = {1, 1, 1, 1, 1};
    enc(narrow ? &tm_w2n : &tm_w2, CU_TENSOR_MAP_DATA_TYPE_BFLOAT16, 5, const_cast<bf16*>(w2), dims, strides, box, es, CU_TENSOR_MAP_INTERLEAVE_NONE,
        narrow ? CU_TENSOR_MAP_SWIZZLE_64B : CU_TENSOR_MAP_SWIZZLE_128B, CU_TENSOR_MAP_L2_PROMOTION_L2_128B, CU_TENSOR_MAP_FLOAT_OOB_FILL_NONE);
  }
  launch(k0_mod_ln, 36 * MODP + 128, 256, 0, false, 1, x, c, wmod);
  launch(k1_qkv, 128, 352, K1_SMEM, USE_PDL, 2, tm_xn, tm_wqkv, wo);
  launch(k2_attn, 132, 512, K2_SMEM, USE_PDL, 1, tm_wmod, c, w1, w2);
  launch(k3_wo, 128, 320, K3_SMEM, USE_PDL, 2, tm_o, tm_wo, tm_x, tm_x2s, tm_h2s);
  launch(k4_mlp1, 128, 384, K4_SMEM, USE_PDL, 2, tm_h2, tm_w1);
  launch(k5_mlp2, 128, 384, K5_SMEM, USE_PDL, 2, tm_H, tm_w2, tm_w2n, tm_out);
}
```

```cpp
#include <cuda_runtime.h>
#include <cuda_bf16.h>
#include <cuda.h>
#include <stdint.h>

namespace {

constexpr int SEQ = 2048, DM = 576, DHEAD = 18, FF = 4608;
constexpr int SLOT_BYTES = SEQ * 48;

typedef __nv_bfloat16 bf16;

__device__ __align__(1024) bf16    g_mod[6 * DM];
#define MODP 2
__device__ __align__(1024) float   g_modp[MODP * 2 * DM];
constexpr int ACT_BYTES = SEQ * DM * 2;
__device__ __align__(1024) uint8_t g_arena[ACT_BYTES + SEQ * FF * 2];
#define g_qkvp (g_arena)
#define g_h2   (reinterpret_cast<bf16*>(g_arena))
#define g_xn   (reinterpret_cast<bf16*>(g_arena + 96 * SLOT_BYTES))
#define g_o    (reinterpret_cast<bf16*>(g_arena + 96 * SLOT_BYTES))
#define g_H    (reinterpret_cast<bf16*>(g_arena + ACT_BYTES))
__device__ __align__(1024) float   g_nrm[64 * 16];
__device__ __align__(1024) bf16    g_woT[DM * DM];
__device__ __align__(1024) uint4   g_stats[SEQ * 8];
__device__ unsigned int g_epoch;

__device__ __forceinline__ uint32_t s2u(const void* p) { return (uint32_t)__cvta_generic_to_shared(p); }
__device__ __forceinline__ void mbar_init(uint32_t b, uint32_t c) { asm volatile("mbarrier.init.shared::cta.b64 [%0], %1;" :: "r"(b), "r"(c) : "memory"); }
__device__ __forceinline__ void mbar_expect(uint32_t b, uint32_t bytes) { asm volatile("mbarrier.arrive.expect_tx.shared::cta.b64 _, [%0], %1;" :: "r"(b), "r"(bytes) : "memory"); }
__device__ __forceinline__ void mbar_arrive(uint32_t b) { asm volatile("mbarrier.arrive.shared::cta.b64 _, [%0];" :: "r"(b) : "memory"); }
__device__ __forceinline__ bool mbar_try(uint32_t b, uint32_t ph) {
  uint32_t ok;
  asm volatile("{\n.reg .pred p;\nmbarrier.try_wait.parity.shared::cta.b64 p, [%1], %2;\nselp.u32 %0, 1, 0, p;\n}" : "=r"(ok) : "r"(b), "r"(ph) : "memory");
  return ok != 0;
}
__device__ __forceinline__ void mbar_wait(uint32_t b, uint32_t ph) {
  if (!mbar_try(b, ph)) {
    for (int n = 0; n < (1 << 22); n++) if (mbar_try(b, ph)) break;
  }
}
__device__ __forceinline__ void fence_barrier_init() { asm volatile("fence.mbarrier_init.release.cluster;" ::: "memory"); }
__device__ __forceinline__ void fence_async_smem() { asm volatile("fence.proxy.async.shared::cta;" ::: "memory"); }
__device__ __forceinline__ void bar_sync(int id, int n) { asm volatile("bar.sync %0, %1;" :: "r"(id), "r"(n) : "memory"); }
__device__ __forceinline__ void pdl_wait() { asm volatile("griddepcontrol.wait;" ::: "memory"); }
__device__ __forceinline__ void pdl_launch() { asm volatile("griddepcontrol.launch_dependents;" ::: "memory"); }
__device__ __forceinline__ void bulk_g2s(uint32_t dst, const void* src, uint32_t bytes, uint32_t bar) {
  asm volatile("cp.async.bulk.shared::cluster.global.mbarrier::complete_tx::bytes [%0], [%1], %2, [%3];" :: "r"(dst), "l"(src), "r"(bytes), "r"(bar) : "memory");
}
__device__ __forceinline__ void bulk_s2g(void* dst, uint32_t src, uint32_t bytes) {
  asm volatile("cp.async.bulk.global.shared::cta.bulk_group [%0], [%1], %2;" :: "l"(dst), "r"(src), "r"(bytes) : "memory");
}
__device__ __forceinline__ void bulk_commit() { asm volatile("cp.async.bulk.commit_group;" ::: "memory"); }
__device__ __forceinline__ void bulk_wait_read() { asm volatile("cp.async.bulk.wait_group.read 0;" ::: "memory"); }
__device__ __forceinline__ void tma2d(uint32_t dst, const CUtensorMap* m, int x, int y, uint32_t bar) {
  asm volatile("cp.async.bulk.tensor.2d.shared::cluster.global.mbarrier::complete_tx::bytes [%0], [%1, {%3, %4}], [%2];"
               :: "r"(dst), "l"(m), "r"(bar), "r"(x), "r"(y) : "memory");
}
__device__ __forceinline__ void tma2d_mc(uint32_t dst, const CUtensorMap* m, int x, int y, uint32_t bar) {
  asm volatile("cp.async.bulk.tensor.2d.shared::cluster.global.mbarrier::complete_tx::bytes.multicast::cluster [%0], [%1, {%3, %4}], [%2], %5;"
               :: "r"(dst), "l"(m), "r"(bar), "r"(x), "r"(y), "h"((uint16_t)3) : "memory");
}
__device__ __forceinline__ void tma5d_mc(uint32_t dst, const CUtensorMap* m, int c0, int c1, int c2, int c3, int c4, uint32_t bar) {
  asm volatile("cp.async.bulk.tensor.5d.shared::cluster.global.mbarrier::complete_tx::bytes.multicast::cluster [%0], [%1, {%3, %4, %5, %6, %7}], [%2], %8;"
               :: "r"(dst), "l"(m), "r"(bar), "r"(c0), "r"(c1), "r"(c2), "r"(c3), "r"(c4), "h"((uint16_t)3) : "memory");
}
__device__ __forceinline__ void tma2d_store(const CUtensorMap* m, uint32_t src, int x, int y) {
  asm volatile("cp.async.bulk.tensor.2d.global.shared::cta.bulk_group [%0, {%2, %3}], [%1];" :: "l"(m), "r"(src), "r"(x), "r"(y) : "memory");
}
__device__ __forceinline__ uint32_t map_cta(uint32_t a, uint32_t cta) { uint32_t r; asm("mapa.shared::cluster.u32 %0, %1, %2;" : "=r"(r) : "r"(a), "r"(cta)); return r; }
__device__ __forceinline__ void mbar_arrive_remote(uint32_t ra) { asm volatile("mbarrier.arrive.shared::cluster.b64 _, [%0];" :: "r"(ra) : "memory"); }
__device__ __forceinline__ void cluster_arrive_relaxed() { asm volatile("barrier.cluster.arrive.relaxed;" ::: "memory"); }
__device__ __forceinline__ void cluster_wait() { asm volatile("barrier.cluster.wait.acquire;" ::: "memory"); }
__device__ __forceinline__ uint32_t cluster_rank() { uint32_t r; asm("mov.u32 %0, %%cluster_ctarank;" : "=r"(r)); return r; }
__device__ __forceinline__ void tmap_prefetch(const CUtensorMap* m) { asm volatile("prefetch.tensormap [%0];" :: "l"(m) : "memory"); }
__device__ __forceinline__ void wg_fence() { asm volatile("wgmma.fence.sync.aligned;" ::: "memory"); }
__device__ __forceinline__ void wg_commit() { asm volatile("wgmma.commit_group.sync.aligned;" ::: "memory"); }
template <int N> __device__ __forceinline__ void wg_wait() { asm volatile("wgmma.wait_group.sync.aligned %0;" :: "n"(N) : "memory"); }
__device__ __forceinline__ uint64_t mkdesc(uint32_t addr, uint32_t lbo, uint32_t sbo, int sw) {
  return (uint64_t)((addr & 0x3FFFF) >> 4) | ((uint64_t)(lbo >> 4) << 16) | ((uint64_t)(sbo >> 4) << 32) | ((uint64_t)sw << 62);
}
template <int N> __device__ __forceinline__ void fence_regs(float (&d)[N]) {
#pragma unroll
  for (int i = 0; i < N; i++) asm volatile("" : "+f"(d[i]) :: "memory");
}
template <int N> __device__ __forceinline__ void fence_regs(uint32_t (&d)[N]) {
#pragma unroll
  for (int i = 0; i < N; i++) asm volatile("" : "+r"(d[i]) :: "memory");
}
__device__ __forceinline__ float ex2(float x) { float y; asm("ex2.approx.ftz.f32 %0, %1;" : "=f"(y) : "f"(x)); return y; }
__device__ __forceinline__ float tanh_fast(float x) { float y; asm("tanh.approx.f32 %0, %1;" : "=f"(y) : "f"(x)); return y; }
__device__ __forceinline__ uint32_t pack_bf16(float lo, float hi) { uint32_t v; asm("cvt.rn.bf16x2.f32 %0, %1, %2;" : "=r"(v) : "f"(hi), "f"(lo)); return v; }
__device__ __forceinline__ float bf_lo(uint32_t v) { return __uint_as_float(v << 16); }
__device__ __forceinline__ float bf_hi(uint32_t v) { return __uint_as_float(v & 0xFFFF0000u); }
__device__ __forceinline__ float bf_round(float x) { return __bfloat162float(__float2bfloat16_rn(x)); }
__device__ __forceinline__ uint32_t hfma2(uint32_t a, uint32_t b, uint32_t c) { uint32_t d; asm("fma.rn.bf16x2 %0, %1, %2, %3;" : "=r"(d) : "r"(a), "r"(b), "r"(c)); return d; }
__device__ __forceinline__ uint32_t hadd2(uint32_t a, uint32_t b) { uint32_t d; asm("add.rn.bf16x2 %0, %1, %2;" : "=r"(d) : "r"(a), "r"(b)); return d; }
__device__ __forceinline__ uint32_t opaque(uint32_t v) { uint32_t r; asm volatile("mov.b32 %0, %1;" : "=r"(r) : "r"(v)); return r; }
__device__ __forceinline__ void ldsm4(uint32_t (&r)[4], uint32_t a) {
  asm volatile("ldmatrix.sync.aligned.m8n8.x4.shared.b16 {%0,%1,%2,%3}, [%4];" : "=r"(r[0]), "=r"(r[1]), "=r"(r[2]), "=r"(r[3]) : "r"(a));
}
__device__ __forceinline__ uint4 lds128(uint32_t a) { uint4 v; asm volatile("ld.shared.v4.b32 {%0,%1,%2,%3}, [%4];" : "=r"(v.x), "=r"(v.y), "=r"(v.z), "=r"(v.w) : "r"(a)); return v; }
__device__ __forceinline__ uint32_t lds32(uint32_t a) { uint32_t v; asm volatile("ld.shared.b32 %0, [%1];" : "=r"(v) : "r"(a)); return v; }
__device__ __forceinline__ void sts32(uint32_t a, uint32_t v) { asm volatile("st.shared.b32 [%0], %1;" :: "r"(a), "r"(v) : "memory"); }
template <int R> __device__ __forceinline__ void reg_inc() { asm volatile("setmaxnreg.inc.sync.aligned.u32 %0;" :: "n"(R)); }
template <int R> __device__ __forceinline__ void reg_dec() { asm volatile("setmaxnreg.dec.sync.aligned.u32 %0;" :: "n"(R)); }

#define TL(k, i)
#define TLT(k, i, t)
#define TLC(k, i, t)

__device__ __forceinline__ void wgmma_rs_n216_tb(float (&d)[108], uint32_t a0, uint32_t a1, uint32_t a2, uint32_t a3, uint64_t db, int sd) {
  asm volatile("{\n.reg .pred p;\nsetp.ne.b32 p, %113, 0;\n"
    "wgmma.mma_async.sync.aligned.m64n216k16.f32.bf16.bf16 "
    "{%0, %1, %2, %3, %4, %5, %6, %7, %8, %9, %10, %11, %12, %13, %14, %15, %16, %17, %18, %19, %20, %21, %22, %23, %24, %25, %26, %27, %28, %29, %30, %31, %32, %33, %34, %35, %36, %37, %38, %39, %40, %41, %42, %43, %44, %45, %46, %47, %48, %49, %50, %51, %52, %53, %54, %55, %56, %57, %58, %59, %60, %61, %62, %63, %64, %65, %66, %67, %68, %69, %70, %71, %72, %73, %74, %75, %76, %77, %78, %79, %80, %81, %82, %83, %84, %85, %86, %87, %88, %89, %90, %91, %92, %93, %94, %95, %96, %97, %98, %99, %100, %101, %102, %103, %104, %105, %106, %107}, {%108,%109,%110,%111}, %112, p, 1, 1, 1;\n}\n"
    : "+f"(d[0]), "+f"(d[1]), "+f"(d[2]), "+f"(d[3]), "+f"(d[4]), "+f"(d[5]), "+f"(d[6]), "+f"(d[7]), "+f"(d[8]), "+f"(d[9]), "+f"(d[10]), "+f"(d[11]), "+f"(d[12]), "+f"(d[13]), "+f"(d[14]), "+f"(d[15]), "+f"(d[16]), "+f"(d[17]), "+f"(d[18]), "+f"(d[19]), "+f"(d[20]), "+f"(d[21]), "+f"(d[22]), "+f"(d[23]), "+f"(d[24]), "+f"(d[25]), "+f"(d[26]), "+f"(d[27]), "+f"(d[28]), "+f"(d[29]), "+f"(d[30]), "+f"(d[31]), "+f"(d[32]), "+f"(d[33]), "+f"(d[34]), "+f"(d[35]), "+f"(d[36]), "+f"(d[37]), "+f"(d[38]), "+f"(d[39]), "+f"(d[40]), "+f"(d[41]), "+f"(d[42]), "+f"(d[43]), "+f"(d[44]), "+f"(d[45]), "+f"(d[46]), "+f"(d[47]), "+f"(d[48]), "+f"(d[49]), "+f"(d[50]), "+f"(d[51]), "+f"(d[52]), "+f"(d[53]), "+f"(d[54]), "+f"(d[55]), "+f"(d[56]), "+f"(d[57]), "+f"(d[58]), "+f"(d[59]), "+f"(d[60]), "+f"(d[61]), "+f"(d[62]), "+f"(d[63]), "+f"(d[64]), "+f"(d[65]), "+f"(d[66]), "+f"(d[67]), "+f"(d[68]), "+f"(d[69]), "+f"(d[70]), "+f"(d[71]), "+f"(d[72]), "+f"(d[73]), "+f"(d[74]), "+f"(d[75]), "+f"(d[76]), "+f"(d[77]), "+f"(d[78]), "+f"(d[79]), "+f"(d[80]), "+f"(d[81]), "+f"(d[82]), "+f"(d[83]), "+f"(d[84]), "+f"(d[85]), "+f"(d[86]), "+f"(d[87]), "+f"(d[88]), "+f"(d[89]), "+f"(d[90]), "+f"(d[91]), "+f"(d[92]), "+f"(d[93]), "+f"(d[94]), "+f"(d[95]), "+f"(d[96]), "+f"(d[97]), "+f"(d[98]), "+f"(d[99]), "+f"(d[100]), "+f"(d[101]), "+f"(d[102]), "+f"(d[103]), "+f"(d[104]), "+f"(d[105]), "+f"(d[106]), "+f"(d[107])
    : "r"(a0), "r"(a1), "r"(a2), "r"(a3), "l"(db), "r"(sd));
}
__device__ __forceinline__ void wgmma_ss_n72(float (&d)[36], uint64_t da, uint64_t db, int sd) {
  asm volatile("{\n.reg .pred p;\nsetp.ne.b32 p, %38, 0;\n"
    "wgmma.mma_async.sync.aligned.m64n72k16.f32.bf16.bf16 "
    "{%0, %1, %2, %3, %4, %5, %6, %7, %8, %9, %10, %11, %12, %13, %14, %15, %16, %17, %18, %19, %20, %21, %22, %23, %24, %25, %26, %27, %28, %29, %30, %31, %32, %33, %34, %35}, %36, %37, p, 1, 1, 0, 0;\n}\n"
    : "+f"(d[0]), "+f"(d[1]), "+f"(d[2]), "+f"(d[3]), "+f"(d[4]), "+f"(d[5]), "+f"(d[6]), "+f"(d[7]), "+f"(d[8]), "+f"(d[9]), "+f"(d[10]), "+f"(d[11]), "+f"(d[12]), "+f"(d[13]), "+f"(d[14]), "+f"(d[15]), "+f"(d[16]), "+f"(d[17]), "+f"(d[18]), "+f"(d[19]), "+f"(d[20]), "+f"(d[21]), "+f"(d[22]), "+f"(d[23]), "+f"(d[24]), "+f"(d[25]), "+f"(d[26]), "+f"(d[27]), "+f"(d[28]), "+f"(d[29]), "+f"(d[30]), "+f"(d[31]), "+f"(d[32]), "+f"(d[33]), "+f"(d[34]), "+f"(d[35])
    : "l"(da), "l"(db), "r"(sd));
}
__device__ __forceinline__ void wgmma_ss_n192_tb(float (&d)[96], uint64_t da, uint64_t db, int sd) {
  asm volatile("{\n.reg .pred p;\nsetp.ne.b32 p, %98, 0;\n"
    "wgmma.mma_async.sync.aligned.m64n192k16.f32.bf16.bf16 "
    "{%0, %1, %2, %3, %4, %5, %6, %7, %8, %9, %10, %11, %12, %13, %14, %15, %16, %17, %18, %19, %20, %21, %22, %23, %24, %25, %26, %27, %28, %29, %30, %31, %32, %33, %34, %35, %36, %37, %38, %39, %40, %41, %42, %43, %44, %45, %46, %47, %48, %49, %50, %51, %52, %53, %54, %55, %56, %57, %58, %59, %60, %61, %62, %63, %64, %65, %66, %67, %68, %69, %70, %71, %72, %73, %74, %75, %76, %77, %78, %79, %80, %81, %82, %83, %84, %85, %86, %87, %88, %89, %90, %91, %92, %93, %94, %95}, %96, %97, p, 1, 1, 0, 1;\n}\n"
    : "+f"(d[0]), "+f"(d[1]), "+f"(d[2]), "+f"(d[3]), "+f"(d[4]), "+f"(d[5]), "+f"(d[6]), "+f"(d[7]), "+f"(d[8]), "+f"(d[9]), "+f"(d[10]), "+f"(d[11]), "+f"(d[12]), "+f"(d[13]), "+f"(d[14]), "+f"(d[15]), "+f"(d[16]), "+f"(d[17]), "+f"(d[18]), "+f"(d[19]), "+f"(d[20]), "+f"(d[21]), "+f"(d[22]), "+f"(d[23]), "+f"(d[24]), "+f"(d[25]), "+f"(d[26]), "+f"(d[27]), "+f"(d[28]), "+f"(d[29]), "+f"(d[30]), "+f"(d[31]), "+f"(d[32]), "+f"(d[33]), "+f"(d[34]), "+f"(d[35]), "+f"(d[36]), "+f"(d[37]), "+f"(d[38]), "+f"(d[39]), "+f"(d[40]), "+f"(d[41]), "+f"(d[42]), "+f"(d[43]), "+f"(d[44]), "+f"(d[45]), "+f"(d[46]), "+f"(d[47]), "+f"(d[48]), "+f"(d[49]), "+f"(d[50]), "+f"(d[51]), "+f"(d[52]), "+f"(d[53]), "+f"(d[54]), "+f"(d[55]), "+f"(d[56]), "+f"(d[57]), "+f"(d[58]), "+f"(d[59]), "+f"(d[60]), "+f"(d[61]), "+f"(d[62]), "+f"(d[63]), "+f"(d[64]), "+f"(d[65]), "+f"(d[66]), "+f"(d[67]), "+f"(d[68]), "+f"(d[69]), "+f"(d[70]), "+f"(d[71]), "+f"(d[72]), "+f"(d[73]), "+f"(d[74]), "+f"(d[75]), "+f"(d[76]), "+f"(d[77]), "+f"(d[78]), "+f"(d[79]), "+f"(d[80]), "+f"(d[81]), "+f"(d[82]), "+f"(d[83]), "+f"(d[84]), "+f"(d[85]), "+f"(d[86]), "+f"(d[87]), "+f"(d[88]), "+f"(d[89]), "+f"(d[90]), "+f"(d[91]), "+f"(d[92]), "+f"(d[93]), "+f"(d[94]), "+f"(d[95])
    : "l"(da), "l"(db), "r"(sd));
}
__device__ __forceinline__ void wgmma_rs_n256_tb(float (&d)[128], uint32_t a0, uint32_t a1, uint32_t a2, uint32_t a3, uint64_t db, int sd) {
  asm volatile("{\n.reg .pred p;\nsetp.ne.b32 p, %133, 0;\n"
    "wgmma.mma_async.sync.aligned.m64n256k16.f32.bf16.bf16 "
    "{%0, %1, %2, %3, %4, %5, %6, %7, %8, %9, %10, %11, %12, %13, %14, %15, %16, %17, %18, %19, %20, %21, %22, %23, %24, %25, %26, %27, %28, %29, %30, %31, %32, %33, %34, %35, %36, %37, %38, %39, %40, %41, %42, %43, %44, %45, %46, %47, %48, %49, %50, %51, %52, %53, %54, %55, %56, %57, %58, %59, %60, %61, %62, %63, %64, %65, %66, %67, %68, %69, %70, %71, %72, %73, %74, %75, %76, %77, %78, %79, %80, %81, %82, %83, %84, %85, %86, %87, %88, %89, %90, %91, %92, %93, %94, %95, %96, %97, %98, %99, %100, %101, %102, %103, %104, %105, %106, %107, %108, %109, %110, %111, %112, %113, %114, %115, %116, %117, %118, %119, %120, %121, %122, %123, %124, %125, %126, %127}, {%128,%129,%130,%131}, %132, p, 1, 1, 1;\n}\n"
    : "+f"(d[0]), "+f"(d[1]), "+f"(d[2]), "+f"(d[3]), "+f"(d[4]), "+f"(d[5]), "+f"(d[6]), "+f"(d[7]), "+f"(d[8]), "+f"(d[9]), "+f"(d[10]), "+f"(d[11]), "+f"(d[12]), "+f"(d[13]), "+f"(d[14]), "+f"(d[15]), "+f"(d[16]), "+f"(d[17]), "+f"(d[18]), "+f"(d[19]), "+f"(d[20]), "+f"(d[21]), "+f"(d[22]), "+f"(d[23]), "+f"(d[24]), "+f"(d[25]), "+f"(d[26]), "+f"(d[27]), "+f"(d[28]), "+f"(d[29]), "+f"(d[30]), "+f"(d[31]), "+f"(d[32]), "+f"(d[33]), "+f"(d[34]), "+f"(d[35]), "+f"(d[36]), "+f"(d[37]), "+f"(d[38]), "+f"(d[39]), "+f"(d[40]), "+f"(d[41]), "+f"(d[42]), "+f"(d[43]), "+f"(d[44]), "+f"(d[45]), "+f"(d[46]), "+f"(d[47]), "+f"(d[48]), "+f"(d[49]), "+f"(d[50]), "+f"(d[51]), "+f"(d[52]), "+f"(d[53]), "+f"(d[54]), "+f"(d[55]), "+f"(d[56]), "+f"(d[57]), "+f"(d[58]), "+f"(d[59]), "+f"(d[60]), "+f"(d[61]), "+f"(d[62]), "+f"(d[63]), "+f"(d[64]), "+f"(d[65]), "+f"(d[66]), "+f"(d[67]), "+f"(d[68]), "+f"(d[69]), "+f"(d[70]), "+f"(d[71]), "+f"(d[72]), "+f"(d[73]), "+f"(d[74]), "+f"(d[75]), "+f"(d[76]), "+f"(d[77]), "+f"(d[78]), "+f"(d[79]), "+f"(d[80]), "+f"(d[81]), "+f"(d[82]), "+f"(d[83]), "+f"(d[84]), "+f"(d[85]), "+f"(d[86]), "+f"(d[87]), "+f"(d[88]), "+f"(d[89]), "+f"(d[90]), "+f"(d[91]), "+f"(d[92]), "+f"(d[93]), "+f"(d[94]), "+f"(d[95]), "+f"(d[96]), "+f"(d[97]), "+f"(d[98]), "+f"(d[99]), "+f"(d[100]), "+f"(d[101]), "+f"(d[102]), "+f"(d[103]), "+f"(d[104]), "+f"(d[105]), "+f"(d[106]), "+f"(d[107]), "+f"(d[108]), "+f"(d[109]), "+f"(d[110]), "+f"(d[111]), "+f"(d[112]), "+f"(d[113]), "+f"(d[114]), "+f"(d[115]), "+f"(d[116]), "+f"(d[117]), "+f"(d[118]), "+f"(d[119]), "+f"(d[120]), "+f"(d[121]), "+f"(d[122]), "+f"(d[123]), "+f"(d[124]), "+f"(d[125]), "+f"(d[126]), "+f"(d[127])
    : "r"(a0), "r"(a1), "r"(a2), "r"(a3), "l"(db), "r"(sd));
}
__device__ __forceinline__ void wgmma_rs_n32_tb(float (&d)[16], uint32_t a0, uint32_t a1, uint32_t a2, uint32_t a3, uint64_t db, int sd) {
  asm volatile("{\n.reg .pred p;\nsetp.ne.b32 p, %21, 0;\n"
    "wgmma.mma_async.sync.aligned.m64n32k16.f32.bf16.bf16 "
    "{%0, %1, %2, %3, %4, %5, %6, %7, %8, %9, %10, %11, %12, %13, %14, %15}, {%16,%17,%18,%19}, %20, p, 1, 1, 1;\n}\n"
    : "+f"(d[0]), "+f"(d[1]), "+f"(d[2]), "+f"(d[3]), "+f"(d[4]), "+f"(d[5]), "+f"(d[6]), "+f"(d[7]), "+f"(d[8]), "+f"(d[9]), "+f"(d[10]), "+f"(d[11]), "+f"(d[12]), "+f"(d[13]), "+f"(d[14]), "+f"(d[15])
    : "r"(a0), "r"(a1), "r"(a2), "r"(a3), "l"(db), "r"(sd));
}
__device__ __forceinline__ void wgmma_rs_n64(float (&d)[32], uint32_t a0, uint32_t a1, uint32_t a2, uint32_t a3, uint64_t db, int sd) {
  asm volatile("{\n.reg .pred p;\nsetp.ne.b32 p, %37, 0;\n"
    "wgmma.mma_async.sync.aligned.m64n64k16.f32.bf16.bf16 "
    "{%0, %1, %2, %3, %4, %5, %6, %7, %8, %9, %10, %11, %12, %13, %14, %15, %16, %17, %18, %19, %20, %21, %22, %23, %24, %25, %26, %27, %28, %29, %30, %31}, {%32,%33,%34,%35}, %36, p, 1, 1, 0;\n}\n"
    : "+f"(d[0]), "+f"(d[1]), "+f"(d[2]), "+f"(d[3]), "+f"(d[4]), "+f"(d[5]), "+f"(d[6]), "+f"(d[7]), "+f"(d[8]), "+f"(d[9]), "+f"(d[10]), "+f"(d[11]), "+f"(d[12]), "+f"(d[13]), "+f"(d[14]), "+f"(d[15]), "+f"(d[16]), "+f"(d[17]), "+f"(d[18]), "+f"(d[19]), "+f"(d[20]), "+f"(d[21]), "+f"(d[22]), "+f"(d[23]), "+f"(d[24]), "+f"(d[25]), "+f"(d[26]), "+f"(d[27]), "+f"(d[28]), "+f"(d[29]), "+f"(d[30]), "+f"(d[31])
    : "r"(a0), "r"(a1), "r"(a2), "r"(a3), "l"(db), "r"(sd));
}
__device__ __forceinline__ void wgmma_rs0_n64(float (&d)[32], uint32_t a0, uint32_t a1, uint32_t a2, uint32_t a3, uint64_t db) {
  asm volatile("{\n.reg .pred p;\nsetp.ne.b32 p, 0, 0;\n"
    "wgmma.mma_async.sync.aligned.m64n64k16.f32.bf16.bf16 "
    "{%0, %1, %2, %3, %4, %5, %6, %7, %8, %9, %10, %11, %12, %13, %14, %15, %16, %17, %18, %19, %20, %21, %22, %23, %24, %25, %26, %27, %28, %29, %30, %31}, {%32,%33,%34,%35}, %36, p, 1, 1, 0;\n}\n"
    : "=f"(d[0]), "=f"(d[1]), "=f"(d[2]), "=f"(d[3]), "=f"(d[4]), "=f"(d[5]), "=f"(d[6]), "=f"(d[7]), "=f"(d[8]), "=f"(d[9]), "=f"(d[10]), "=f"(d[11]), "=f"(d[12]), "=f"(d[13]), "=f"(d[14]), "=f"(d[15]), "=f"(d[16]), "=f"(d[17]), "=f"(d[18]), "=f"(d[19]), "=f"(d[20]), "=f"(d[21]), "=f"(d[22]), "=f"(d[23]), "=f"(d[24]), "=f"(d[25]), "=f"(d[26]), "=f"(d[27]), "=f"(d[28]), "=f"(d[29]), "=f"(d[30]), "=f"(d[31])
    : "r"(a0), "r"(a1), "r"(a2), "r"(a3), "l"(db));
}
__device__ __forceinline__ void wgmma_rs_n24_tb(float (&d)[12], uint32_t a0, uint32_t a1, uint32_t a2, uint32_t a3, uint64_t db, int sd) {
  asm volatile("{\n.reg .pred p;\nsetp.ne.b32 p, %17, 0;\n"
    "wgmma.mma_async.sync.aligned.m64n24k16.f32.bf16.bf16 "
    "{%0, %1, %2, %3, %4, %5, %6, %7, %8, %9, %10, %11}, {%12,%13,%14,%15}, %16, p, 1, 1, 1;\n}\n"
    : "+f"(d[0]), "+f"(d[1]), "+f"(d[2]), "+f"(d[3]), "+f"(d[4]), "+f"(d[5]), "+f"(d[6]), "+f"(d[7]), "+f"(d[8]), "+f"(d[9]), "+f"(d[10]), "+f"(d[11])
    : "r"(a0), "r"(a1), "r"(a2), "r"(a3), "l"(db), "r"(sd));
}

__device__ __forceinline__ float silu_ref(float c) { return bf_round(c / (1.0f + __expf(-c))); }

__global__ void __launch_bounds__(256) k0_mod_ln(const bf16* __restrict__ x, const bf16* __restrict__ c, const bf16* __restrict__ wmod,
                                                 const bf16* __restrict__ wqkv) {
  __shared__ float red[8][32];
  pdl_launch();
  const int t = threadIdx.x, warp = t >> 5, lane = t & 31;
  if (blockIdx.x < 36 * MODP) {
    constexpr int ROWS = DM / MODP, NJ = (ROWS + 63) / 64;
    const int b = blockIdx.x, strip = b % 36, half = b / 36, cq = t & 3, kr = t >> 2;
    if (b == 0 && t == 0) g_epoch = g_epoch + 1;
    uint4 wv[NJ]; float cs[NJ];
#pragma unroll
    for (int j = 0; j < NJ; j++) {
      const int kk = kr + 64 * j, k = half * ROWS + kk;
      if (kk < ROWS) { wv[j] = __ldg(reinterpret_cast<const uint4*>(wmod + (size_t)k * (6 * DM) + strip * 32 + cq * 8)); cs[j] = __bfloat162float(c[k]); }
      else { wv[j] = make_uint4(0, 0, 0, 0); cs[j] = 0.f; }
    }
    float acc[8];
#pragma unroll
    for (int i = 0; i < 8; i++) acc[i] = 0.f;
#pragma unroll
    for (int j = 0; j < NJ; j++) {
      const float s = silu_ref(cs[j]);
      const uint32_t w[4] = {wv[j].x, wv[j].y, wv[j].z, wv[j].w};
#pragma unroll
      for (int i = 0; i < 4; i++) { acc[2 * i] = fmaf(s, bf_lo(w[i]), acc[2 * i]); acc[2 * i + 1] = fmaf(s, bf_hi(w[i]), acc[2 * i + 1]); }
    }
#pragma unroll
    for (int o = 4; o < 32; o <<= 1) {
#pragma unroll
      for (int i = 0; i < 8; i++) acc[i] += __shfl_xor_sync(0xffffffffu, acc[i], o);
    }
    if (lane < 4) {
#pragma unroll
      for (int i = 0; i < 8; i++) red[warp][lane * 8 + i] = acc[i];
    }
    __syncthreads();
    if (t < 32) {
      float s = 0.f;
#pragma unroll
      for (int w = 0; w < 8; w++) s += red[w][t];
      g_modp[half * 1152 + strip * 32 + t] = s;
    }
  } else {
    const int r0 = (blockIdx.x - 36 * MODP) * 16 + warp * 2;
    const uint32_t* xr = reinterpret_cast<const uint32_t*>(x + (size_t)r0 * DM);
    uint32_t xv[2][9];
#pragma unroll
    for (int j = 0; j < 9; j++) { xv[0][j] = __ldg(xr + lane + 32 * j); xv[1][j] = __ldg(xr + 288 + lane + 32 * j); }
    if (t == 0)
      asm volatile("cp.async.bulk.prefetch.L2.global [%0], %1;"
                   :: "l"(reinterpret_cast<const char*>(wqkv) + (size_t)(blockIdx.x - 36 * MODP) * (DM * 3 * DM * 2 / 128)), "r"(DM * 3 * DM * 2 / 128) : "memory");
    float s0 = 0.f, s1 = 0.f;
#pragma unroll
    for (int j = 0; j < 9; j++) { s0 += bf_lo(xv[0][j]) + bf_hi(xv[0][j]); s1 += bf_lo(xv[1][j]) + bf_hi(xv[1][j]); }
#pragma unroll
    for (int o = 16; o; o >>= 1) { s0 += __shfl_xor_sync(0xffffffffu, s0, o); s1 += __shfl_xor_sync(0xffffffffu, s1, o); }
    const float m0 = s0 * (1.0f / DM), m1 = s1 * (1.0f / DM);
    float v0 = 0.f, v1 = 0.f;
#pragma unroll
    for (int j = 0; j < 9; j++) {
      float d;
      d = bf_lo(xv[0][j]) - m0; v0 = fmaf(d, d, v0); d = bf_hi(xv[0][j]) - m0; v0 = fmaf(d, d, v0);
      d = bf_lo(xv[1][j]) - m1; v1 = fmaf(d, d, v1); d = bf_hi(xv[1][j]) - m1; v1 = fmaf(d, d, v1);
    }
#pragma unroll
    for (int o = 16; o; o >>= 1) { v0 += __shfl_xor_sync(0xffffffffu, v0, o); v1 += __shfl_xor_sync(0xffffffffu, v1, o); }
    const float rs0 = 1.0f / sqrtf(v0 * (1.0f / DM) + 1e-5f), rs1 = 1.0f / sqrtf(v1 * (1.0f / DM) + 1e-5f);
    uint32_t* o32 = reinterpret_cast<uint32_t*>(g_xn + (size_t)r0 * DM);
#pragma unroll
    for (int j = 0; j < 9; j++) {
      o32[lane + 32 * j] = pack_bf16((bf_lo(xv[0][j]) - m0) * rs0, (bf_hi(xv[0][j]) - m0) * rs0);
      o32[288 + lane + 32 * j] = pack_bf16((bf_lo(xv[1][j]) - m1) * rs1, (bf_hi(xv[1][j]) - m1) * rs1);
    }
  }
}

__device__ __forceinline__ void mod_tail(const bf16* __restrict__ c, const CUtensorMap* tm_wmod, int part, uint8_t* smem, uint32_t bar) {
  const int t = threadIdx.x;
  const uint32_t sb = s2u(smem);
  float* sc = reinterpret_cast<float*>(smem + 2 * 73728);
  float* red = sc + 576;
  auto fill = [&](int b) {
    mbar_expect(bar + 8 * (b & 1), 73728);
    for (int j = 0; j < 3; j++) tma2d(sb + (b & 1) * 73728 + j * 24576, tm_wmod, 1152 + part * 576 + j * 192, b * 64, bar + 8 * (b & 1));
  };
  if (t == 0) { fill(0); fill(1); }
  for (int k = t; k < DM; k += 512) sc[k] = silu_ref(__bfloat162float(c[k]));
  __syncthreads();
  const int cg = t % 72, rg = t / 72;
  float acc[8];
#pragma unroll
  for (int i = 0; i < 8; i++) acc[i] = 0.f;
#pragma unroll 1
  for (int b = 0; b < 9; b++) {
    mbar_wait(bar + 8 * (b & 1), (b >> 1) & 1);
    if (rg < 7) {
#pragma unroll 5
      for (int r = rg; r < 64; r += 7) {
        const uint4 v = lds128(sb + (b & 1) * 73728 + (cg / 24) * 24576 + r * 384 + (cg % 24) * 16);
        const float s = sc[b * 64 + r];
        acc[0] = fmaf(s, bf_lo(v.x), acc[0]); acc[1] = fmaf(s, bf_hi(v.x), acc[1]); acc[2] = fmaf(s, bf_lo(v.y), acc[2]); acc[3] = fmaf(s, bf_hi(v.y), acc[3]);
        acc[4] = fmaf(s, bf_lo(v.z), acc[4]); acc[5] = fmaf(s, bf_hi(v.z), acc[5]); acc[6] = fmaf(s, bf_lo(v.w), acc[6]); acc[7] = fmaf(s, bf_hi(v.w), acc[7]);
      }
    }
    __syncthreads();
    if (t == 0 && b + 2 < 9) fill(b + 2);
  }
  if (rg < 7) {
#pragma unroll
    for (int i = 0; i < 8; i++) red[rg * 576 + cg * 8 + i] = acc[i];
  }
  __syncthreads();
  for (int col = t; col < 576; col += 512) {
    float s = 0.f;
#pragma unroll
    for (int r = 0; r < 7; r++) s += red[r * 576 + col];
    g_mod[1152 + part * 576 + col] = __float2bfloat16_rn(s);
  }
}

constexpr int K1_NST = 5;
constexpr int K1_A = 0, K1_W = 147456, K1_MOD = K1_W + K1_NST * 16384, K1_RED = K1_MOD + 2304, K1_BAR = K1_RED + 256;
constexpr int K1_SMEM = K1_BAR + 8 * (10 + 2 * K1_NST);
#define QSCALE (0.23570226039551584f * 1.4426950408889634f)
#define POLY_MASK 0xFC
__host__ __device__ constexpr bool poly_block(int b) {
  return (POLY_MASK >> b) & 1;
}
constexpr uint32_t KPAD_POLY = 0x42FE47C0u;
constexpr uint32_t VPAD_ONE  = 0x00003F80u;

template <int ST>
__device__ __forceinline__ void k1_load_a(uint32_t (&A)[2][4], const uint32_t (&aoff)[4], uint32_t mtab) {
#pragma unroll
  for (int j = 0; j < 2; j++) {
    ldsm4(A[j], aoff[(ST & 1) * 2 + j] + (ST >> 1) * 16384);
    const uint4 m = lds128(mtab + (ST * 2 + j) * 64);
    A[j][0] = hfma2(A[j][0], m.x, m.z); A[j][1] = hfma2(A[j][1], m.x, m.z);
    A[j][2] = hfma2(A[j][2], m.y, m.w); A[j][3] = hfma2(A[j][3], m.y, m.w);
  }
}
template <int ST>
__device__ __forceinline__ void k1_steps(float (&acc)[108], uint32_t (&A)[3][2][4], const uint32_t (&aoff)[4], uint32_t mtab, uint64_t db0,
                                         uint32_t bx, uint32_t bwf, uint32_t rbe, bool releaser) {
  if constexpr (ST < 18) {
    constexpr int s = ST % K1_NST;
    mbar_wait(bwf + 8 * s, (ST / K1_NST) & 1);
    fence_regs(A[ST % 3][0]); fence_regs(A[ST % 3][1]);
    wg_fence();
#pragma unroll
    for (int j = 0; j < 2; j++)
      wgmma_rs_n216_tb(acc, A[ST % 3][j][0], A[ST % 3][j][1], A[ST % 3][j][2], A[ST % 3][j][3], db0 + (uint64_t)(s * 1024 + j * 128), 1);
    wg_commit();
    if constexpr (ST + 1 < 18) {
      if constexpr (((ST + 1) & 1) == 0) mbar_wait(bx + 8 * ((ST + 1) >> 1), 0);
      k1_load_a<ST + 1>(A[(ST + 1) % 3], aoff, mtab);
    }
    if constexpr (ST > 0) {
      wg_wait<1>();
      if (ST - 1 + K1_NST < 18 && releaser) mbar_arrive_remote(rbe + 8 * ((ST - 1) % K1_NST));
    }
    k1_steps<ST + 1>(acc, A, aoff, mtab, db0, bx, bwf, rbe, releaser);
  }
}

__host__ __device__ constexpr int k1_off(int I, int Q) {
  const int col = 8 * I + 2 * Q, sl = col / 18, d = col % 18;
  return sl * 6144 + (d >> 3) * 128 + (d & 7) * 2 - 4 * Q;
}
template <int I>
__device__ __forceinline__ void k1_stage_block(const float (&acc)[108], uint32_t base, int q4, int nq) {
  uint32_t a = base + k1_off(I, 0);
  if constexpr (k1_off(I, 1) != k1_off(I, 0)) a += q4 >= 1 ? k1_off(I, 1) - k1_off(I, 0) : 0;
  if constexpr (k1_off(I, 2) != k1_off(I, 1)) a += q4 >= 2 ? k1_off(I, 2) - k1_off(I, 1) : 0;
  if constexpr (k1_off(I, 3) != k1_off(I, 2)) a += q4 >= 3 ? k1_off(I, 3) - k1_off(I, 2) : 0;
  constexpr int s0 = (8 * I) / 18, s3 = (8 * I + 6) / 18, qs = s0 == s3 ? 4 : (18 * s3 - 8 * I) / 2;
  const float sc = ((q4 >= qs ? s3 : s0) < nq) ? QSCALE : 1.0f;
  sts32(a, pack_bf16(acc[4 * I] * sc, acc[4 * I + 1] * sc));
  sts32(a + 384, pack_bf16(acc[4 * I + 2] * sc, acc[4 * I + 3] * sc));
}
template <int G>
__device__ __forceinline__ void k1_stage_group(const float (&acc)[108], uint32_t base, uint32_t pbase, uint32_t kpad, int q4, int nt, int rb, int tid,
                                               uint32_t sb) {
  const int nq = 32 - 12 * nt;
  k1_stage_block<9 * G + 0>(acc, base, q4, nq); k1_stage_block<9 * G + 1>(acc, base, q4, nq); k1_stage_block<9 * G + 2>(acc, base, q4, nq);
  k1_stage_block<9 * G + 3>(acc, base, q4, nq); k1_stage_block<9 * G + 4>(acc, base, q4, nq); k1_stage_block<9 * G + 5>(acc, base, q4, nq);
  k1_stage_block<9 * G + 6>(acc, base, q4, nq); k1_stage_block<9 * G + 7>(acc, base, q4, nq); k1_stage_block<9 * G + 8>(acc, base, q4, nq);
#pragma unroll
  for (int i = 0; i < 2; i++) {
    const int slot = nt * 12 + 4 * G + 2 * i + (tid >> 7);
    const uint32_t pad = slot >= 64 ? VPAD_ONE : (slot >= 32 ? kpad : 0u);
    const uint32_t a = pbase + (4 * G + 2 * i) * 6144;
    sts32(a + 4, pad);
    asm volatile("st.shared.v2.b32 [%0], {%1, %1};" :: "r"(a + 8), "r"(0u) : "memory");
  }
  fence_async_smem();
  bar_sync(1, 256);
  if (tid == 0) {
#pragma unroll
    for (int sl = 4 * G; sl < 4 * G + 4; sl++)
      bulk_s2g(g_qkvp + (size_t)(nt * 12 + sl) * SLOT_BYTES + (size_t)rb * 6144, sb + sl * 6144, 6144);
    bulk_commit();
  }
}

__device__ __forceinline__ void transpose_wo_block(const bf16* __restrict__ wo, int kb, int nb, int lane) {
  const int h = lane & 1;
  uint4 v[2][8];
#pragma unroll
  for (int u = 0; u < 2; u++)
#pragma unroll
    for (int g = 0; g < 8; g++) v[u][g] = __ldg(reinterpret_cast<const uint4*>(wo + (size_t)(kb * 64 + u * 32 + lane) * DM + nb * 64 + g * 8));
  uint32_t* dst = reinterpret_cast<uint32_t*>(g_woT) + (size_t)(nb * 64 + 4 * h) * (DM / 2) + kb * 32 + (lane >> 1);
#pragma unroll
  for (int u = 0; u < 2; u++)
#pragma unroll
    for (int g = 0; g < 8; g++) {
      const uint32_t r0 = __shfl_xor_sync(0xffffffffu, h ? v[u][g].x : v[u][g].z, 1), r1 = __shfl_xor_sync(0xffffffffu, h ? v[u][g].y : v[u][g].w, 1);
      const uint32_t o0 = h ? v[u][g].z : v[u][g].x, o1 = h ? v[u][g].w : v[u][g].y;
      const uint32_t l0 = h ? r0 : o0, l1 = h ? r1 : o1, h0 = h ? o0 : r0, h1 = h ? o1 : r1;
      uint32_t* d = dst + (size_t)g * 8 * (DM / 2) + u * 16;
      d[0 * (DM / 2)] = __byte_perm(l0, h0, 0x5410); d[1 * (DM / 2)] = __byte_perm(l0, h0, 0x7632);
      d[2 * (DM / 2)] = __byte_perm(l1, h1, 0x5410); d[3 * (DM / 2)] = __byte_perm(l1, h1, 0x7632);
    }
}

__global__ void __launch_bounds__(352, 1) k1_qkv(const __grid_constant__ CUtensorMap tm_xn, const __grid_constant__ CUtensorMap tm_w, const bf16* __restrict__ wo) {
  extern __shared__ __align__(1024) uint8_t smem[];
  const uint32_t sb = s2u(smem);
  const int tid = threadIdx.x, nt = (blockIdx.x >> 1) & 7, rb = (blockIdx.x >> 4) * 2 + (blockIdx.x & 1);
  const uint32_t bx = sb + K1_BAR, bmp = bx + 72, bwf = bmp + 8, bwe = bwf + 8 * K1_NST;
  TL(1, 0);
  if (tid == 256) {
    for (int i = 0; i < 10; i++) mbar_init(bx + 8 * i, 1);
    for (int i = 0; i < K1_NST; i++) { mbar_init(bwf + 8 * i, 1); mbar_init(bwe + 8 * i, 4); }
    fence_barrier_init();
    tmap_prefetch(&tm_xn); tmap_prefetch(&tm_w);
  }
  __syncthreads();
  cluster_arrive_relaxed();
  pdl_launch();
  if (tid >= 320) {
    cluster_wait();
    if (blockIdx.x < 81) transpose_wo_block(wo, blockIdx.x / 9, blockIdx.x % 9, tid & 31);
    return;
  }
  if (tid >= 288) {
    auto load_x = [&](int c) { mbar_expect(bx + 8 * c, 16384); tma2d(sb + K1_A + c * 16384, &tm_xn, c * 64, rb * 128, bx + 8 * c); };
    if (tid == 288) {
      pdl_wait();
      mbar_expect(bmp, MODP * 2 * DM * 4); bulk_g2s(sb + K1_A + 8 * 16384, g_modp, MODP * 2 * DM * 4, bmp);
      load_x(0); load_x(1); load_x(2);
    }
    __syncwarp();
    cluster_wait();
    if (tid == 288)
      for (int c = 3; c < 9; c++) { mbar_wait(bx + 8 * (c - 3), 0); if (c == 8) mbar_wait(bwe, 0); load_x(c); }
    return;
  }
  if (tid >= 256) {
    cluster_wait();
    if (tid == 256) {
      const int rank = cluster_rank();
      auto load_w = [&](int st) {
        const int s = st % K1_NST;
        mbar_expect(bwf + 8 * s, 16384);
        for (int g = 2 * rank; g < 2 * rank + 2; g++) tma2d_mc(sb + K1_W + s * 16384 + g * 4096, &tm_w, nt * 216 + g * 64, st * 32, bwf + 8 * s);
      };
      for (int st = 0; st < K1_NST; st++) load_w(st);
      for (int st = K1_NST; st < 18; st++) {
        mbar_wait(bwe + 8 * (st % K1_NST), (st / K1_NST - 1) & 1);
        load_w(st);
      }
    }
    __syncwarp();
    cluster_arrive_relaxed(); cluster_wait();
    return;
  }
  cluster_wait();
  const int wg = __reduce_max_sync(0xffffffffu, (unsigned)tid >> 7), wtid = tid & 127, warp = (tid >> 5) & 3, lane = tid & 31, g = lane >> 2, q4 = lane & 3;
  const uint32_t rbe = map_cta(bwe, wtid & 1);
  TL(1, 1);
  {
    const float2* mp = reinterpret_cast<const float2*>(smem + K1_A + 8 * 16384);
    mbar_wait(bmp, 0);
    for (int i = tid; i < 288; i += 256) {
      float2 s0 = mp[i], c0 = mp[288 + i];
#pragma unroll
      for (int p = 1; p < MODP; p++) {
        const float2 s1 = mp[p * 576 + i], c1 = mp[p * 576 + 288 + i];
        s0.x += s1.x; s0.y += s1.y; c0.x += c1.x; c0.y += c1.y;
      }
      const uint32_t a = sb + K1_MOD + (i >> 3) * 64 + (i & 3) * 16 + ((i >> 2) & 1) * 4;
      sts32(a, hadd2(pack_bf16(c0.x, c0.y), 0x3F803F80u));
      sts32(a + 8, pack_bf16(s0.x, s0.y));
    }
  }
  bar_sync(1, 256);
  TL(1, 4);
  uint32_t aoff[4];
  {
    const int r = wg * 64 + warp * 16 + (lane & 7) + ((lane >> 3) & 1) * 8;
#pragma unroll
    for (int j = 0; j < 4; j++) aoff[j] = opaque(sb + K1_A + r * 128 + (((2 * j + (lane >> 4)) ^ (lane & 7)) << 4));
  }
  const uint32_t mtab = opaque(sb + K1_MOD + q4 * 16);
  float acc[108];
#pragma unroll
  for (int i = 0; i < 108; i++) acc[i] = 0.f;
  const uint64_t db0 = mkdesc(sb + K1_W, 4096, 1024, 1);
  uint32_t A[3][2][4];
  mbar_wait(bx, 0);
  TL(1, 5);
  k1_load_a<0>(A[0], aoff, mtab);
  k1_steps<0>(acc, A, aoff, mtab, db0, bx, bwf, rbe, wtid < 2);
  wg_wait<0>();
  fence_regs(acc);
  cluster_arrive_relaxed();
  TL(1, 2);
  bar_sync(1, 256);
  {
    const int tok = wg * 64 + warp * 16 + g;
    const uint32_t base = opaque(sb + (tok >> 3) * 384 + (tok & 7) * 16 + q4 * 4);
    const int tk = tid & 127;
    const uint32_t pbase = opaque(sb + (tid >> 7) * 6144 + (tk >> 3) * 384 + (tk & 7) * 16 + 256);
    const uint32_t kpad = poly_block((tk >> 3) & 7) ? KPAD_POLY : 0u;
    k1_stage_group<0>(acc, base, pbase, kpad, q4, nt, rb, tid, sb);
    k1_stage_group<1>(acc, base, pbase, kpad, q4, nt, rb, tid, sb);
    k1_stage_group<2>(acc, base, pbase, kpad, q4, nt, rb, tid, sb);
  }
  TL(1, 3);
  if (nt * 12 < 64) {
    const int tok = tid & 127;
    float* red = reinterpret_cast<float*>(smem + K1_RED);
#pragma unroll
    for (int i = 0; i < 6; i++) {
      const int sl = (tid >> 7) + 2 * i;
      const uint32_t a = sb + sl * 6144 + (tok >> 3) * 384 + (tok & 7) * 16;
      const uint4 v0 = lds128(a), v1 = lds128(a + 128);
      const uint32_t v2 = lds32(a + 256);
      float n2 = 0.f;
      const uint32_t w[9] = {v0.x, v0.y, v0.z, v0.w, v1.x, v1.y, v1.z, v1.w, v2};
#pragma unroll
      for (int j = 0; j < 9; j++) { n2 = fmaf(bf_lo(w[j]), bf_lo(w[j]), n2); n2 = fmaf(bf_hi(w[j]), bf_hi(w[j]), n2); }
      const uint32_t mx = __reduce_max_sync(0xffffffffu, __float_as_uint(n2) & 0x7FFFFFFFu);
      if (lane == 0) red[sl * 4 + warp] = __uint_as_float(mx);
    }
    bar_sync(1, 256);
    if (tid >= 32 && tid < 44) {
      const int sl = tid - 32, slot = nt * 12 + sl;
      const uint32_t* r = reinterpret_cast<const uint32_t*>(red) + sl * 4;
      if (slot < 64) g_nrm[slot * 16 + rb] = __uint_as_float(max(max(r[0], r[1]), max(r[2], r[3])));
    }
  }
  if (tid == 0) bulk_wait_read();
  TL(1, 7);
  cluster_wait();
}

constexpr int K2_K = 0, K2_V = SLOT_BYTES, K2_Q = 2 * SLOT_BYTES, K2_BAR = K2_Q + 512 * 48, K2_SMEM = K2_BAR + 8 * 19;
constexpr uint32_t EXP_C2 = 0x3EA93EA9u, EXP_C1 = 0x3B4E3B4Eu, EXP_C0 = 0x3F2C3F2Cu;
constexpr int K2_TD = 8 * 384 / 16;

__device__ __forceinline__ void attn_qk(float (&S)[32], const uint32_t (&q)[8], uint64_t kd) {
  wgmma_rs0_n64(S, q[0], q[1], q[2], q[3], kd);
  wgmma_rs_n64(S, q[4], q[5], q[6], q[7], kd + 16, 1);
}
__device__ __forceinline__ void attn_pv(float (&O)[12], const uint32_t (&P)[16], uint64_t vd) {
#pragma unroll
  for (int kk = 0; kk < 4; kk++) wgmma_rs_n24_tb(O, P[4 * kk], P[4 * kk + 1], P[4 * kk + 2], P[4 * kk + 3], vd + kk * 48, 1);
}
__device__ __forceinline__ void attn_exp(float (&S)[32], uint32_t c2, uint32_t cone) {
#pragma unroll
  for (int b = 0; b < 8; b++) {
    if (poly_block(b)) {
#pragma unroll
      for (int h = 0; h < 2; h++) {
        uint32_t w, y;
        asm("prmt.b32 %0, %1, %2, 0x5410;" : "=r"(w) : "r"(__float_as_uint(S[4 * b + 2 * h])), "r"(__float_as_uint(S[4 * b + 2 * h + 1])));
        asm("lop3.b32 %0, %1, 0x007F007F, %2, 0xEA;" : "=r"(y) : "r"(w), "r"(cone));
        const uint32_t p = hfma2(hfma2(y, c2, EXP_C1), y, EXP_C0);
        S[4 * b + 2 * h] = __uint_as_float(w);
        S[4 * b + 2 * h + 1] = __uint_as_float(p);
      }
    } else {
#pragma unroll
      for (int j = 0; j < 4; j++) S[4 * b + j] = ex2(S[4 * b + j]);
    }
  }
}
__device__ __forceinline__ void attn_pack(const float (&S)[32], uint32_t (&P)[16]) {
#pragma unroll
  for (int i = 0; i < 16; i++) {
    if (poly_block(i >> 1)) asm("lop3.b32 %0, %1, %2, 0xFF80FF80, 0xE4;" : "=r"(P[i]) : "r"(__float_as_uint(S[2 * i])), "r"(__float_as_uint(S[2 * i + 1])));
    else P[i] = pack_bf16(S[2 * i], S[2 * i + 1]);
  }
}

__device__ __forceinline__ void attn_load_chunk(uint32_t sb, uint32_t bar, const uint8_t* Kg, int c) {
  mbar_expect(bar + 8 * c, 2 * 6144);
  bulk_g2s(sb + K2_K + c * 6144, Kg + c * 6144, 6144, bar + 8 * c);
  bulk_g2s(sb + K2_V + c * 6144, Kg + (size_t)32 * SLOT_BYTES + c * 6144, 6144, bar + 8 * c);
}

template <bool WAIT>
__device__ __forceinline__ void attn_fast_pass(float (&O)[12], const uint32_t (&q)[8], uint64_t kd, uint64_t vd, uint32_t bar) {
  float S[32]; uint32_t P[16];
  const uint32_t c2 = opaque(EXP_C2), cone = opaque(0x3F803F80u);
  if (WAIT) mbar_wait(bar, 0);
  wg_fence();
  attn_qk(S, q, kd);
  wg_commit();
  wg_wait<0>();
  fence_regs(S);
  attn_exp(S, c2, cone);
  attn_pack(S, P);
  auto step = [&]() {
    kd += K2_TD;
    fence_regs(P); fence_regs(O);
    wg_fence();
    attn_qk(S, q, kd);
    wg_commit();
    attn_pv(O, P, vd);
    wg_commit();
    vd += K2_TD;
    wg_wait<1>();
    fence_regs(S);
    attn_exp(S, c2, cone);
    fence_regs(S);
    wg_wait<0>();
    fence_regs(S); fence_regs(O);
    attn_pack(S, P);
  };
#pragma unroll 1
  for (int c = 1; c < 16; c++) {
    if (WAIT) mbar_wait(bar + 8 * c, 0);
    step();
    step();
  }
  step();
  fence_regs(P); fence_regs(O);
  wg_fence();
  attn_pv(O, P, vd);
  wg_commit();
  wg_wait<0>();
  fence_regs(O);
}

__device__ __forceinline__ void attn_safe_pass(float (&O)[12], const uint32_t (&q)[8], uint64_t kd, uint64_t vd, uint32_t bar) {
  float S[32]; uint32_t P[16];
  float m0 = -INFINITY, m1 = -INFINITY;
  mbar_wait(bar, 0);
#pragma unroll 1
  for (int j = 0; j < 32; j++) {
    mbar_wait(bar + 8 * min((j + 1) >> 1, 15), 0);
    wg_fence();
    attn_qk(S, q, kd);
    wg_commit();
    wg_wait<0>();
    fence_regs(S);
    float x0 = m0, x1 = m1;
#pragma unroll
    for (int b = 0; b < 8; b++) { x0 = fmaxf(x0, fmaxf(S[4 * b], S[4 * b + 1])); x1 = fmaxf(x1, fmaxf(S[4 * b + 2], S[4 * b + 3])); }
    x0 = fmaxf(x0, __shfl_xor_sync(0xffffffffu, x0, 1)); x0 = fmaxf(x0, __shfl_xor_sync(0xffffffffu, x0, 2));
    x1 = fmaxf(x1, __shfl_xor_sync(0xffffffffu, x1, 1)); x1 = fmaxf(x1, __shfl_xor_sync(0xffffffffu, x1, 2));
    const float a0 = ex2(m0 - x0), a1 = ex2(m1 - x1);
    m0 = x0; m1 = x1;
#pragma unroll
    for (int b = 0; b < 3; b++) { O[4 * b] *= a0; O[4 * b + 1] *= a0; O[4 * b + 2] *= a1; O[4 * b + 3] *= a1; }
#pragma unroll
    for (int b = 0; b < 8; b++) {
      P[2 * b] = pack_bf16(ex2(S[4 * b] - m0), ex2(S[4 * b + 1] - m0));
      P[2 * b + 1] = pack_bf16(ex2(S[4 * b + 2] - m1), ex2(S[4 * b + 3] - m1));
    }
    fence_regs(P); fence_regs(O);
    wg_fence();
    attn_pv(O, P, vd);
    wg_commit();
    wg_wait<0>();
    fence_regs(O);
    kd += K2_TD; vd += K2_TD;
  }
}

__global__ void __launch_bounds__(512, 1) k2_attn(const __grid_constant__ CUtensorMap tm_wmod, const bf16* __restrict__ cvec,
                                                   const bf16* __restrict__ w1, const bf16* __restrict__ w2) {
  extern __shared__ __align__(1024) uint8_t smem[];
  const uint32_t sb = s2u(smem);
  const int head = blockIdx.x >> 2, qg = blockIdx.x & 3;
  const int tid = threadIdx.x, wg = __reduce_max_sync(0xffffffffu, (unsigned)tid >> 7), warp = (tid >> 5) & 3, lane = tid & 31, g = lane >> 2, q4 = lane & 3;
  const uint32_t bar = sb + K2_BAR;
  TL(2, 0);
  if (tid == 0) {
    for (int i = 0; i < 18; i++) mbar_init(bar + 8 * i, 1);
    fence_barrier_init();
  }
  __syncthreads();
  if (blockIdx.x >= 128) {
    mod_tail(cvec, &tm_wmod, blockIdx.x - 128, smem, bar);
    pdl_wait();
    return;
  }
  pdl_wait();
  pdl_launch();
  TL(2, 3);
  if ((tid >> 5) == 1) {
    uint32_t nv = 0;
    if (lane < 16) nv = __float_as_uint(__ldcg(&g_nrm[(32 + head) * 16 + lane]));
    else if (lane < 20) nv = __float_as_uint(__ldcg(&g_nrm[head * 16 + qg * 4 + lane - 16]));
    const uint32_t km = __reduce_max_sync(0xffffffffu, lane < 16 ? nv : 0u), qm = __reduce_max_sync(0xffffffffu, lane < 16 ? 0u : nv);
    if (lane == 0) sts32(bar + 8 * 18, __uint_as_float(km) * __uint_as_float(qm) <= 4096.0f ? 1u : 0u);
  }
  const uint8_t* Kg = g_qkvp + (size_t)(32 + head) * SLOT_BYTES;
  bool fast;
  {
    const uint8_t* Qg = g_qkvp + (size_t)head * SLOT_BYTES + (size_t)qg * 512 * 48;
    if (tid == 0) {
      mbar_expect(bar + 8 * 16, 4 * 3072);
      for (int w = 0; w < 4; w++) bulk_g2s(sb + K2_Q + w * 6144, Qg + w * 6144, 3072, bar + 8 * 16);
      for (int c = 0; c < 2; c++) attn_load_chunk(sb, bar, Kg, c);
    }
    __syncthreads();
    fast = lds32(bar + 8 * 18) != 0;
    if (tid == 32) {
      for (int c = 2; c < 16; c++) attn_load_chunk(sb, bar, Kg, c);
      mbar_expect(bar + 8 * 17, 4 * 3072);
      for (int w = 0; w < 4; w++) bulk_g2s(sb + K2_Q + w * 6144 + 3072, Qg + w * 6144 + 3072, 3072, bar + 8 * 17);
    }
    __syncwarp();
  }
  TL(2, 1);
  const uint64_t kd = mkdesc(sb + K2_K, 128, 384, 0);
  const uint64_t vd = mkdesc(sb + K2_V, 384, 128, 0);
#pragma unroll 1
  for (int it = 0; it < 2; it++) {
    const int qt = wg * 2 + it;
    mbar_wait(bar + 8 * (16 + it), 0);
    if (it == 0) TL(2, 4);
    uint32_t q[8];
    {
      const uint32_t base = sb + K2_Q + (qt * 8 + warp * 2) * 384 + g * 16 + q4 * 4;
#pragma unroll
      for (int j = 0; j < 3; j++) { q[2 * j] = lds32(base + j * 128); q[2 * j + 1] = lds32(base + 384 + j * 128); }
      if (fast && q4 == 1) { q[4] = 0x3F803F80u; q[5] = 0x3F803F80u; }
      q[6] = opaque(0u); q[7] = opaque(0u);
    }
    if (it == 1 && tid == 0) {
      const char* a = reinterpret_cast<const char*>(w1) + (size_t)blockIdx.x * (DM * FF * 2 / 128);
      const char* b = reinterpret_cast<const char*>(w2) + (size_t)blockIdx.x * (DM * FF * 2 / 128);
      asm volatile("cp.async.bulk.prefetch.L2.global [%0], %1;" :: "l"(a), "r"(DM * FF * 2 / 128) : "memory");
      asm volatile("cp.async.bulk.prefetch.L2.global [%0], %1;" :: "l"(b), "r"(DM * FF * 2 / 128) : "memory");
    }
    float O[12];
#pragma unroll
    for (int i = 0; i < 12; i++) O[i] = 0.f;
    if (fast) {
      if (it == 0) attn_fast_pass<true>(O, q, kd, vd, bar);
      else attn_fast_pass<false>(O, q, kd, vd, bar);
    } else {
      attn_safe_pass(O, q, kd, vd, bar);
    }
    const float l0 = __shfl_sync(0xffffffffu, O[8], (lane & ~3) | 1), l1 = __shfl_sync(0xffffffffu, O[10], (lane & ~3) | 1);
    const float r0 = __frcp_rn(l0), r1 = __frcp_rn(l1);
    const int row = qg * 512 + qt * 64 + warp * 16 + g;
    uint32_t* o0 = reinterpret_cast<uint32_t*>(g_o + (size_t)row * DM + head * DHEAD + q4 * 2);
    uint32_t* o1 = o0 + 8 * DM / 2;
    o0[0] = pack_bf16(O[0] * r0, O[1] * r0);  o1[0] = pack_bf16(O[2] * r1, O[3] * r1);
    o0[4] = pack_bf16(O[4] * r0, O[5] * r0);  o1[4] = pack_bf16(O[6] * r1, O[7] * r1);
    if (q4 == 0) { o0[8] = pack_bf16(O[8] * r0, O[9] * r0);  o1[8] = pack_bf16(O[10] * r1, O[11] * r1); }
  }
  TL(2, 7);
}

constexpr int K3_A = 0, K3_W = 147456, K3_X = K3_W, K3_MOD = K3_W + 9 * 9216, K3_BAR = K3_MOD + 3 * 144 + 16;
constexpr int K3_SMEM = K3_BAR + 8 * (9 + 9 + 3);

__global__ void __launch_bounds__(320, 1) k3_wo(const __grid_constant__ CUtensorMap tm_o, const __grid_constant__ CUtensorMap tm_wo,
                                                const __grid_constant__ CUtensorMap tm_x, const __grid_constant__ CUtensorMap tm_x2,
                                                const __grid_constant__ CUtensorMap tm_h2) {
  extern __shared__ __align__(1024) uint8_t smem[];
  const uint32_t sb = s2u(smem);
  const int tid = threadIdx.x, nt = blockIdx.x & 7, rb = blockIdx.x >> 3;
  const uint32_t bw = sb + K3_BAR, baf = bw + 72, bxb = baf + 72, bmd = bxb + 8, bxe = bmd + 8;
  TL(3, 0);
  if (tid == 256) {
    for (int i = 0; i < 20; i++) mbar_init(bw + 8 * i, 1);
    mbar_init(bxe, 2);
    fence_barrier_init();
    tmap_prefetch(&tm_o); tmap_prefetch(&tm_wo); tmap_prefetch(&tm_x); tmap_prefetch(&tm_x2); tmap_prefetch(&tm_h2);
  }
  __syncthreads();
  cluster_arrive_relaxed();
  pdl_launch();
  if (tid >= 288) {
    if (tid == 288)
      for (int c = 0; c < 9; c++) { mbar_expect(bw + 8 * c, 9216); tma2d(sb + K3_W + c * 9216, &tm_wo, c * 64, nt * 72, bw + 8 * c); }
    __syncwarp();
    cluster_wait();
    return;
  }
  if (tid >= 256) {
    cluster_wait();
    if (tid == 256) {
      const int rank = cluster_rank();
      pdl_wait();
      for (int c = 0; c < 9; c++) {
        mbar_expect(baf + 8 * c, 16384);
        tma2d_mc(sb + K3_A + c * 16384 + rank * 8192, &tm_o, c * 64, rb * 128 + rank * 64, baf + 8 * c);
      }
      mbar_expect(bmd, 3 * 144);
      for (int v = 0; v < 3; v++) bulk_g2s(sb + K3_MOD + v * 144, g_mod + (2 + v) * DM + nt * 72, 144, bmd);
      mbar_wait(bxe, 0);
      mbar_expect(bxb, 18432); tma2d(sb + K3_X, &tm_x, nt * 72, rb * 128, bxb);
    }
    __syncwarp();
    cluster_arrive_relaxed(); cluster_wait();
    return;
  }
  const int wg = __reduce_max_sync(0xffffffffu, (unsigned)tid >> 7), wtid = tid & 127, warp = (tid >> 5) & 3, lane = tid & 31, g = lane >> 2, q4 = lane & 3;
  const int lrow = wg * 64 + warp * 16 + g;
  cluster_wait();
  pdl_wait();
  TL(3, 1);
  const uint32_t tag = __ldcg(&g_epoch);
  float acc[36];
#pragma unroll
  for (int i = 0; i < 36; i++) acc[i] = 0.f;
  const uint64_t da0 = mkdesc(sb + K3_A + wg * 8192, 16, 1024, 1);
  const uint64_t db0 = mkdesc(sb + K3_W, 16, 1024, 1);
#pragma unroll 1
  for (int c = 0; c < 9; c++) {
    mbar_wait(bw + 8 * c, 0);
    mbar_wait(baf + 8 * c, 0);
    wg_fence();
#pragma unroll
    for (int j = 0; j < 4; j++) wgmma_ss_n72(acc, da0 + (uint64_t)(c * 1024 + j * 2), db0 + (uint64_t)(c * 576 + j * 2), 1);
    wg_commit();
    if (c == 2) { wg_wait<1>(); if (wtid == 0) mbar_arrive(bxe); }
  }
  wg_wait<0>();
  fence_regs(acc);
  cluster_arrive_relaxed();
  TL(3, 2);
  mbar_wait(bmd, 0);
  mbar_wait(bxb, 0);
  const uint32_t xa = sb + K3_X + lrow * 144 + q4 * 4, ma = sb + K3_MOD + q4 * 4;
  float s0 = 0.f, s1 = 0.f;
#pragma unroll
  for (int i = 0; i < 9; i++) {
    const uint32_t x0 = lds32(xa + 16 * i), x1 = lds32(xa + 8 * 144 + 16 * i), ga = lds32(ma + 16 * i);
    const float g0 = bf_lo(ga), g1 = bf_hi(ga);
    const uint32_t p0 = pack_bf16(fmaf(g0, acc[4 * i], bf_lo(x0)), fmaf(g1, acc[4 * i + 1], bf_hi(x0)));
    const uint32_t p1 = pack_bf16(fmaf(g0, acc[4 * i + 2], bf_lo(x1)), fmaf(g1, acc[4 * i + 3], bf_hi(x1)));
    sts32(xa + 16 * i, p0); sts32(xa + 8 * 144 + 16 * i, p1);
    acc[4 * i] = bf_lo(p0); acc[4 * i + 1] = bf_hi(p0); acc[4 * i + 2] = bf_lo(p1); acc[4 * i + 3] = bf_hi(p1);
    s0 += acc[4 * i] + acc[4 * i + 1]; s1 += acc[4 * i + 2] + acc[4 * i + 3];
  }
  s0 += __shfl_xor_sync(0xffffffffu, s0, 1); s1 += __shfl_xor_sync(0xffffffffu, s1, 1);
  s0 += __shfl_xor_sync(0xffffffffu, s0, 2); s1 += __shfl_xor_sync(0xffffffffu, s1, 2);
  const float m0 = s0 * (1.0f / 72), m1 = s1 * (1.0f / 72);
  float v0 = 0.f, v1 = 0.f;
#pragma unroll
  for (int i = 0; i < 9; i++) {
    float d;
    d = acc[4 * i] - m0; v0 = fmaf(d, d, v0); d = acc[4 * i + 1] - m0; v0 = fmaf(d, d, v0);
    d = acc[4 * i + 2] - m1; v1 = fmaf(d, d, v1); d = acc[4 * i + 3] - m1; v1 = fmaf(d, d, v1);
  }
  v0 += __shfl_xor_sync(0xffffffffu, v0, 1); v1 += __shfl_xor_sync(0xffffffffu, v1, 1);
  v0 += __shfl_xor_sync(0xffffffffu, v0, 2); v1 += __shfl_xor_sync(0xffffffffu, v1, 2);
  if (q4 < 2) {
    const float mm = q4 ? m1 : m0, vv = q4 ? v1 : v0;
    asm volatile("st.relaxed.gpu.global.v2.b64 [%0], {%1, %2};"
                 :: "l"(&g_stats[(rb * 8 + nt) * 128 + lrow + 8 * q4]), "l"(((uint64_t)tag << 32) | __float_as_uint(mm)), "l"(((uint64_t)tag << 32) | __float_as_uint(vv)) : "memory");
  }
  fence_async_smem();
  bar_sync(1, 256);
  TL(3, 3);
  if (tid == 0) { tma2d_store(&tm_x2, sb + K3_X, nt * 72, rb * 128); bulk_commit(); }
  float mean0, mean1, rs0, rs1;
  {
    uint64_t w[8];
    const uint4* pa = &g_stats[(rb * 8 + 2 * q4) * 128 + lrow];
    for (int it = 0; it < (1 << 20); it++) {
      asm volatile("ld.relaxed.gpu.global.v2.b64 {%0, %1}, [%2];" : "=l"(w[0]), "=l"(w[1]) : "l"(pa) : "memory");
      asm volatile("ld.relaxed.gpu.global.v2.b64 {%0, %1}, [%2];" : "=l"(w[2]), "=l"(w[3]) : "l"(pa + 128) : "memory");
      asm volatile("ld.relaxed.gpu.global.v2.b64 {%0, %1}, [%2];" : "=l"(w[4]), "=l"(w[5]) : "l"(pa + 8) : "memory");
      asm volatile("ld.relaxed.gpu.global.v2.b64 {%0, %1}, [%2];" : "=l"(w[6]), "=l"(w[7]) : "l"(pa + 136) : "memory");
      bool ok = true;
#pragma unroll
      for (int j = 0; j < 8; j++) ok = ok && (uint32_t)(w[j] >> 32) == tag;
      if (__all_sync(0xffffffffu, ok)) break;
      __nanosleep(200);
    }
    const float ax = __uint_as_float((uint32_t)w[0]), ay = __uint_as_float((uint32_t)w[1]), az = __uint_as_float((uint32_t)w[2]), aw = __uint_as_float((uint32_t)w[3]);
    const float bx = __uint_as_float((uint32_t)w[4]), by = __uint_as_float((uint32_t)w[5]), bz = __uint_as_float((uint32_t)w[6]), bw_ = __uint_as_float((uint32_t)w[7]);
    float sa = ax + az, sb_ = bx + bz;
    sa += __shfl_xor_sync(0xffffffffu, sa, 1); sb_ += __shfl_xor_sync(0xffffffffu, sb_, 1);
    sa += __shfl_xor_sync(0xffffffffu, sa, 2); sb_ += __shfl_xor_sync(0xffffffffu, sb_, 2);
    mean0 = sa * 0.125f; mean1 = sb_ * 0.125f;
    float ma2 = ay + aw + 72.f * ((ax - mean0) * (ax - mean0) + (az - mean0) * (az - mean0));
    float mb2 = by + bw_ + 72.f * ((bx - mean1) * (bx - mean1) + (bz - mean1) * (bz - mean1));
    ma2 += __shfl_xor_sync(0xffffffffu, ma2, 1); mb2 += __shfl_xor_sync(0xffffffffu, mb2, 1);
    ma2 += __shfl_xor_sync(0xffffffffu, ma2, 2); mb2 += __shfl_xor_sync(0xffffffffu, mb2, 2);
    rs0 = rsqrtf(ma2 * (1.0f / DM) + 1e-5f); rs1 = rsqrtf(mb2 * (1.0f / DM) + 1e-5f);
  }
  TL(3, 4);
  {
    const uint32_t ha = sb + K3_A + lrow * 144 + q4 * 4;
#pragma unroll
    for (int i = 0; i < 9; i++) {
      const uint32_t c1p = hadd2(lds32(ma + 288 + 16 * i), 0x3F803F80u), sh = lds32(ma + 144 + 16 * i);
      sts32(ha + 16 * i, hfma2(hfma2(pack_bf16((acc[4 * i] - mean0) * rs0, (acc[4 * i + 1] - mean0) * rs0), c1p, sh), 0x3F003F00u, 0x80008000u));
      sts32(ha + 8 * 144 + 16 * i, hfma2(hfma2(pack_bf16((acc[4 * i + 2] - mean1) * rs1, (acc[4 * i + 3] - mean1) * rs1), c1p, sh), 0x3F003F00u, 0x80008000u));
    }
  }
  fence_async_smem();
  bar_sync(1, 256);
  if (tid == 0) { tma2d_store(&tm_h2, sb + K3_A, nt * 72, rb * 128); bulk_commit(); bulk_wait_read(); }
  TL(3, 7);
  cluster_wait();
}

constexpr int K4_BK = 64;
constexpr int K4_KS = K4_BK / 16;
constexpr int K4_SPT = 576 / K4_BK;
constexpr int K4_NST = 3 * 64 / K4_BK;
constexpr int K4_STB = K4_BK * 384;
constexpr int K4_A = 0, K4_B = 147456, K4_BAR = K4_B + K4_NST * K4_STB, K4_SMEM = K4_BAR + 8 * (9 + 2 * K4_NST) + 8;

__device__ __forceinline__ uint32_t silu2(uint32_t v, uint32_t m16, uint32_t mhi) {
  const float lo = __uint_as_float(v * m16), hi = __uint_as_float(v & mhi);
  return pack_bf16(fmaf(lo, tanh_fast(lo), lo), fmaf(hi, tanh_fast(hi), hi));
}
template <int P>
__device__ __forceinline__ void k4_epi(const uint32_t (&pk)[48], uint32_t go, bf16* hp) {
  const uint32_t m16 = go << 16, mhi = 0u - m16;
  constexpr int B = 8 * (P >> 1) + (P & 1);
  uint4 r;
  r.x = silu2(pk[B], m16, mhi); r.y = silu2(pk[B + 2], m16, mhi); r.z = silu2(pk[B + 4], m16, mhi); r.w = silu2(pk[B + 6], m16, mhi);
  asm volatile("st.global.v4.b32 [%0], {%1,%2,%3,%4};" :: "l"(hp + (P & 1) * 8 * FF + 32 * (P >> 1)), "r"(r.x), "r"(r.y), "r"(r.z), "r"(r.w) : "memory");
}
template <int P0, int N>
__device__ __forceinline__ void k4_epi_n(const uint32_t (&pk)[48], uint32_t go, bf16* hp) {
  if constexpr (N > 0) { k4_epi<P0>(pk, go, hp); k4_epi_n<P0 + 1, N - 1>(pk, go, hp); }
}
__host__ __device__ constexpr int k4_first(int i) { return (i * 12 + 8) / 9; }

template <int T, int I>
__device__ __forceinline__ void k4_steps(float (&acc)[96], const uint32_t (&pk)[48], uint64_t da0, uint64_t db0, uint32_t ba, uint32_t bbf,
                                         uint32_t rbe, int wtid, bf16* hp) {
  if constexpr (I < K4_SPT) {
    constexpr int st = T * K4_SPT + I, s = st % K4_NST, k0 = I * K4_KS;
    if (T == 0 && (k0 & 3) == 0) mbar_wait(ba + 8 * (k0 >> 2), 0);
    mbar_wait(bbf + 8 * s, (st / K4_NST) & 1);
    wg_fence();
#pragma unroll
    for (int j = 0; j < K4_KS; j++)
      wgmma_ss_n192_tb(acc, da0 + (uint64_t)(((k0 + j) >> 2) * 1024 + ((k0 + j) & 3) * 2), db0 + (uint64_t)(s * (K4_STB / 16) + j * 128), (I | j) != 0);
    wg_commit();
    if constexpr (I > 0) {
      wg_wait<1>();
      if (st - 1 + K4_NST < 3 * K4_SPT && wtid < 2) mbar_arrive_remote(rbe + 8 * ((st - 1) % K4_NST));
    }
    if constexpr (T > 0 && k4_first(I + 1) > k4_first(I)) {
      const uint32_t go = mbar_try(ba, 0);
      k4_epi_n<k4_first(I), k4_first(I + 1) - k4_first(I)>(pk, go, hp);
    }
    k4_steps<T, I + 1>(acc, pk, da0, db0, ba, bbf, rbe, wtid, hp);
  }
}
template <int T>
__device__ __forceinline__ void k4_tile(float (&acc)[96], const uint32_t (&pk)[48], uint64_t da0, uint64_t db0, uint32_t ba, uint32_t bbf,
                                        uint32_t rbe, int wtid, bf16* hprev) {
  k4_steps<T, 0>(acc, pk, da0, db0, ba, bbf, rbe, wtid, hprev);
  wg_wait<0>();
  fence_regs(acc);
  if (T * K4_SPT + K4_SPT - 1 + K4_NST < 3 * K4_SPT && wtid < 2) mbar_arrive_remote(rbe + 8 * ((T * K4_SPT + K4_SPT - 1) % K4_NST));
}
__device__ __forceinline__ void k4_pack(const float (&acc)[96], uint32_t (&pk)[48]) {
#pragma unroll
  for (int i = 0; i < 48; i++) pk[i] = pack_bf16(acc[2 * i], acc[2 * i + 1]);
}

__global__ void __launch_bounds__(384, 1) k4_mlp1(const __grid_constant__ CUtensorMap tm_h2, const __grid_constant__ CUtensorMap tm_w1,
                                                  const bf16* __restrict__ w2) {
  extern __shared__ __align__(1024) uint8_t smem[];
  const uint32_t sb = s2u(smem);
  const int tid = threadIdx.x, rb = blockIdx.x & 15, fs = blockIdx.x >> 4;
  const uint32_t ba = sb + K4_BAR, bbf = ba + 72, bbe = bbf + 8 * K4_NST;
  TL(4, 0);
  if (tid == 0) {
    for (int i = 0; i < 9; i++) mbar_init(ba + 8 * i, 1);
    for (int i = 0; i < K4_NST; i++) { mbar_init(bbf + 8 * i, 1); mbar_init(bbe + 8 * i, 4); }
    fence_barrier_init();
    tmap_prefetch(&tm_h2); tmap_prefetch(&tm_w1);
  }
  __syncthreads();
  cluster_arrive_relaxed();
  pdl_launch();
  if (tid < 128) {
    reg_dec<40>();
    if (tid >= 32 && tid < 64) {
      auto load_a = [&](int c) { mbar_expect(ba + 8 * c, 16384); tma2d(sb + K4_A + c * 16384, &tm_h2, c * 64, rb * 128, ba + 8 * c); };
      if (tid == 32) {
        pdl_wait();
        for (int c = 0; c < 4; c++) load_a(c);
      }
      __syncwarp();
      cluster_wait();
      if (tid == 32)
        for (int c = 4; c < 9; c++) { mbar_wait(ba + 8 * (c - 4), 0); load_a(c); }
    } else {
      cluster_wait();
      if (tid == 0) {
        const int rank = cluster_rank();
        for (int st = 0; st < 3 * K4_SPT; st++) {
          const int s = st % K4_NST, t = st / K4_SPT, i = st % K4_SPT;
          if (st >= K4_NST) mbar_wait(bbe + 8 * s, (st / K4_NST - 1) & 1);
          mbar_expect(bbf + 8 * s, K4_STB);
          for (int g = 0; g < 3; g++)
            tma2d_mc(sb + K4_B + s * K4_STB + g * (K4_STB / 3) + rank * (K4_STB / 6), &tm_w1, fs * 576 + t * 192 + g * 64, i * K4_BK + rank * (K4_BK / 2), bbf + 8 * s);
        }
        cluster_arrive_relaxed(); cluster_wait();
      }
    }
  } else {
    reg_inc<232>();
    const int wg = __reduce_max_sync(0xffffffffu, ((unsigned)tid >> 7) - 1), wtid = tid & 127, warp = (tid >> 5) & 3, lane = tid & 31;
    const uint64_t da0 = mkdesc(sb + K4_A + wg * 8192, 16, 1024, 1);
    const uint64_t db0 = mkdesc(sb + K4_B, K4_STB / 3, 1024, 1);
    cluster_wait();
    const uint32_t rbe = map_cta(bbe, wtid & 1);
    bf16* hp = g_H + (size_t)(rb * 128 + wg * 64 + warp * 16 + (lane >> 2)) * FF + fs * 576 + (lane & 3) * 8;
    float acc[96]; uint32_t pk[48];
#pragma unroll
    for (int i = 0; i < 96; i++) acc[i] = 0.f;
    TLT(4, 1, 128); TLC(4, 3, 128);
    k4_tile<0>(acc, pk, da0, db0, ba, bbf, rbe, wtid, hp);
    k4_pack(acc, pk);
    k4_tile<1>(acc, pk, da0, db0, ba, bbf, rbe, wtid, hp);
    k4_pack(acc, pk);
    k4_tile<2>(acc, pk, da0, db0, ba, bbf, rbe, wtid, hp + 192);
    cluster_arrive_relaxed();
    TLT(4, 2, 128); TLC(4, 4, 128);
    k4_pack(acc, pk);
    k4_epi_n<0, 12>(pk, 1u, hp + 384);
    TLT(4, 7, 128);
    cluster_wait();
  }
}

constexpr int K5_NST = 4;
constexpr int K5_STAGE = 16384 + 36864;
constexpr int K5_GB = K5_NST * K5_STAGE, K5_BAR = K5_GB + 576, K5_SMEM = K5_BAR + 8 * (2 * K5_NST + 1);

template <int I> __device__ __forceinline__ float k5_acc(const float (&a)[128], const float (&b)[16]) { if constexpr (I < 128) return a[I]; else return b[I - 128]; }

template <int QD, int I>
__device__ __forceinline__ void k5_stage(const float (&a)[128], const float (&b)[16], uint32_t dst, uint32_t gbs) {
  if constexpr (I < 9) {
    constexpr int B = 9 * QD + I;
    const uint32_t gb = lds32(gbs + B * 16);
    const float g0 = bf_lo(gb), g1 = bf_hi(gb);
    sts32(dst + I * 16, pack_bf16(k5_acc<4 * B>(a, b) * g0, k5_acc<4 * B + 1>(a, b) * g1));
    sts32(dst + 8 * 144 + I * 16, pack_bf16(k5_acc<4 * B + 2>(a, b) * g0, k5_acc<4 * B + 3>(a, b) * g1));
    k5_stage<QD, I + 1>(a, b, dst, gbs);
  }
}
template <int QD>
__device__ __forceinline__ void k5_quarter(const float (&a)[128], const float (&b)[16], uint32_t sb, uint32_t dst, uint32_t gbs, int wg, int wtid,
                                           const CUtensorMap* tm, int col, int row) {
  k5_stage<QD, 0>(a, b, dst + QD * 18432, gbs);
  fence_async_smem();
  bar_sync(2 + wg, 128);
  if (wtid == 0) {
    asm volatile("cp.reduce.async.bulk.tensor.2d.global.shared::cta.add.tile.bulk_group [%0, {%2, %3}], [%1];"
                 :: "l"(tm), "r"(sb + QD * 18432 + wg * 9216), "r"(col + QD * 72), "r"(row) : "memory");
    bulk_commit();
  }
}

__global__ void __launch_bounds__(384, 1) k5_mlp2(const __grid_constant__ CUtensorMap tm_h, const __grid_constant__ CUtensorMap tm_w2,
                                                  const __grid_constant__ CUtensorMap tm_w2n, const __grid_constant__ CUtensorMap tm_out) {
  extern __shared__ __align__(1024) uint8_t smem[];
  const uint32_t sb = s2u(smem);
  const int tid = threadIdx.x, rb = blockIdx.x & 15, nh = (blockIdx.x >> 4) & 1, ks = blockIdx.x >> 5;
  const uint32_t bf = sb + K5_BAR, be = bf + 8 * K5_NST, bg = be + 8 * K5_NST;
  TL(5, 0);
  if (tid == 0) {
    for (int i = 0; i < K5_NST; i++) { mbar_init(bf + 8 * i, 1); mbar_init(be + 8 * i, 4); }
    mbar_init(bg, 1);
    fence_barrier_init();
    tmap_prefetch(&tm_h); tmap_prefetch(&tm_w2); tmap_prefetch(&tm_w2n); tmap_prefetch(&tm_out);
  }
  __syncthreads();
  cluster_arrive_relaxed(); cluster_wait();
  const int rank = cluster_rank();
  if (tid < 128) {
    reg_dec<40>();
    if (tid == 0) {
      auto load_b = [&](int st) {
        const int s = st % K5_NST;
        mbar_expect(bf + 8 * s, K5_STAGE);
        for (int g = 2 * rank; g < 2 * rank + 2; g++)
          tma5d_mc(sb + s * K5_STAGE + 16384 + g * 8192, &tm_w2, nh * 288 + g * 64, 0, 0, 0, (ks * 18 + st) * 2, bf + 8 * s);
        if (rank == 1) tma5d_mc(sb + s * K5_STAGE + 16384 + 32768, &tm_w2n, nh * 288 + 256, 0, 0, 0, (ks * 18 + st) * 2, bf + 8 * s);
      };
      load_b(0);
      pdl_wait();
      for (int st = 0; st < 18; st++) {
        const int s = st % K5_NST;
        if (st >= K5_NST) mbar_wait(be + 8 * s, (st / K5_NST - 1) & 1);
        if (st >= 1) load_b(st);
        tma2d(sb + s * K5_STAGE, &tm_h, (ks * 18 + st) * 64, rb * 128, bf + 8 * s);
        if (st == K5_NST) { mbar_expect(bg, 576); bulk_g2s(sb + K5_GB, g_mod + 5 * DM + nh * 288, 576, bg); }
      }
      cluster_arrive_relaxed(); cluster_wait();
    }
  } else {
    reg_inc<232>();
    const int ctid = tid - 128, wg = __reduce_max_sync(0xffffffffu, (unsigned)ctid >> 7), wtid = tid & 127, warp = (tid >> 5) & 3, lane = tid & 31, g = lane >> 2, q4 = lane & 3;
    float a[128], b[16];
#pragma unroll
    for (int i = 0; i < 128; i++) a[i] = 0.f;
#pragma unroll
    for (int i = 0; i < 16; i++) b[i] = 0.f;
    const uint64_t db0 = mkdesc(sb + 16384, 8192, 1024, 1);
    const uint64_t dn0 = mkdesc(sb + 16384 + 32768, 4096, 512, 2);
    const uint32_t rbe = map_cta(be, wtid & 1);
    uint32_t aoff[4];
    {
      const int r = wg * 64 + warp * 16 + (lane & 7) + ((lane >> 3) & 1) * 8;
#pragma unroll
      for (int j = 0; j < 4; j++) aoff[j] = sb + r * 128 + (((2 * j + (lane >> 4)) ^ (lane & 7)) << 4);
    }
    uint32_t A0[4][4], A1[4][4];
    auto step = [&](uint32_t (&A)[4][4], int st) {
      const int s = st % K5_NST;
      mbar_wait(bf + 8 * s, (st / K5_NST) & 1);
#pragma unroll
      for (int j = 0; j < 4; j++) ldsm4(A[j], aoff[j] + s * K5_STAGE);
      fence_regs(A[0]); fence_regs(A[1]); fence_regs(A[2]); fence_regs(A[3]);
      wg_fence();
#pragma unroll
      for (int j = 0; j < 4; j++) {
        wgmma_rs_n256_tb(a, A[j][0], A[j][1], A[j][2], A[j][3], db0 + (uint64_t)(s * (K5_STAGE / 16) + j * 128), 1);
        wgmma_rs_n32_tb(b, A[j][0], A[j][1], A[j][2], A[j][3], dn0 + (uint64_t)(s * (K5_STAGE / 16) + j * 64), 1);
      }
      wg_commit();
      if (st > 0) {
        wg_wait<1>();
        if (st - 1 + K5_NST < 18 && wtid < 2) mbar_arrive_remote(rbe + 8 * ((st - 1) % K5_NST));
      }
    };
#pragma unroll 1
    for (int st = 0; st < 18; st += 2) { step(A0, st); step(A1, st + 1); }
    wg_wait<0>();
    fence_regs(a); fence_regs(b);
    cluster_arrive_relaxed();
    TLT(5, 2, 128);
    mbar_wait(bg, 0);
    bar_sync(1, 256);
    const uint32_t dst = sb + (wg * 64 + warp * 16 + g) * 144 + q4 * 4, gbs = sb + K5_GB + q4 * 4;
    k5_quarter<0>(a, b, sb, dst, gbs, wg, wtid, &tm_out, nh * 288, rb * 128 + wg * 64);
    k5_quarter<1>(a, b, sb, dst, gbs, wg, wtid, &tm_out, nh * 288, rb * 128 + wg * 64);
    k5_quarter<2>(a, b, sb, dst, gbs, wg, wtid, &tm_out, nh * 288, rb * 128 + wg * 64);
    k5_quarter<3>(a, b, sb, dst, gbs, wg, wtid, &tm_out, nh * 288, rb * 128 + wg * 64);
    TLT(5, 3, 128);
    if (wtid == 0) bulk_wait_read();
    TLT(5, 7, 128);
    cluster_wait();
  }
}

}

typedef CUresult (*EncodeTiledFn)(CUtensorMap*, CUtensorMapDataType, cuuint32_t, void*, const cuuint64_t*, const cuuint64_t*, const cuuint32_t*,
                                  const cuuint32_t*, CUtensorMapInterleave, CUtensorMapSwizzle, CUtensorMapL2promotion, CUtensorMapFloatOOBfill);

static void make_map2d(EncodeTiledFn enc, CUtensorMap* m, const void* base, int cols, int rows, int box_cols, int box_rows, CUtensorMapSwizzle sw) {
  cuuint64_t dims[2] = {(cuuint64_t)cols, (cuuint64_t)rows};
  cuuint64_t strides[1] = {(cuuint64_t)cols * 2};
  cuuint32_t box[2] = {(cuuint32_t)box_cols, (cuuint32_t)box_rows};
  cuuint32_t es[2] = {1, 1};
  enc(m, CU_TENSOR_MAP_DATA_TYPE_BFLOAT16, 2, const_cast<void*>(base), dims, strides, box, es, CU_TENSOR_MAP_INTERLEAVE_NONE, sw,
      CU_TENSOR_MAP_L2_PROMOTION_L2_128B, CU_TENSOR_MAP_FLOAT_OOB_FILL_NONE);
}

template <typename... KArgs, typename... Args>
static void launch(void (*kern)(KArgs...), int grid, int block, int smem, bool pdl, int cluster, Args... args) {
  cudaLaunchConfig_t cfg = {};
  cfg.gridDim = dim3(grid); cfg.blockDim = dim3(block); cfg.dynamicSmemBytes = smem; cfg.stream = cudaStreamPerThread;
  cudaLaunchAttribute at[2];
  int n = 0;
  if (pdl) { at[n].id = cudaLaunchAttributeProgrammaticStreamSerialization; at[n].val.programmaticStreamSerializationAllowed = 1; n++; }
  if (cluster > 1) { at[n].id = cudaLaunchAttributeClusterDimension; at[n].val.clusterDim.x = cluster; at[n].val.clusterDim.y = 1; at[n].val.clusterDim.z = 1; n++; }
  cfg.attrs = at; cfg.numAttrs = n;
  cudaLaunchKernelEx(&cfg, kern, KArgs(args)...);
}

#define USE_PDL 1

extern "C" void kernel_launch(void* const* d_in, const int* in_sizes, int n_in, void* d_out, int out_size) {
  (void)in_sizes; (void)n_in; (void)out_size;
  const bf16* x    = (const bf16*)d_in[0];
  const bf16* wqkv = (const bf16*)d_in[1];
  const bf16* wo   = (const bf16*)d_in[2];
  const bf16* w1   = (const bf16*)d_in[4];
  const bf16* w2   = (const bf16*)d_in[5];
  const bf16* c    = (const bf16*)d_in[6];
  const bf16* wmod = (const bf16*)d_in[7];
  bf16* out = (bf16*)d_out;

  static EncodeTiledFn enc = nullptr;
  if (!enc) {
    void* fn = nullptr; cudaDriverEntryPointQueryResult qr;
    cudaGetDriverEntryPoint("cuTensorMapEncodeTiled", &fn, cudaEnableDefault, &qr);
    enc = (EncodeTiledFn)fn;
    cudaFuncSetAttribute(k1_qkv, cudaFuncAttributeMaxDynamicSharedMemorySize, K1_SMEM);
    cudaFuncSetAttribute(k2_attn, cudaFuncAttributeMaxDynamicSharedMemorySize, K2_SMEM);
    cudaFuncSetAttribute(k3_wo, cudaFuncAttributeMaxDynamicSharedMemorySize, K3_SMEM);
    cudaFuncSetAttribute(k4_mlp1, cudaFuncAttributeMaxDynamicSharedMemorySize, K4_SMEM);
    cudaFuncSetAttribute(k5_mlp2, cudaFuncAttributeMaxDynamicSharedMemorySize, K5_SMEM);
  }
  void *p_arena, *p_woT;
  cudaGetSymbolAddress(&p_arena, g_arena); cudaGetSymbolAddress(&p_woT, g_woT);
  void* p_h2 = p_arena;
  void* p_xn = (uint8_t*)p_arena + 96 * SLOT_BYTES;
  void* p_o = p_xn;
  void* p_H = (uint8_t*)p_arena + ACT_BYTES;
  CUtensorMap tm_xn, tm_wqkv, tm_o, tm_wo, tm_x, tm_x2s, tm_h2s, tm_h2, tm_w1, tm_H, tm_w2, tm_w2n, tm_out, tm_wmod;
  make_map2d(enc, &tm_xn, p_xn, DM, SEQ, 64, 128, CU_TENSOR_MAP_SWIZZLE_128B);
  make_map2d(enc, &tm_wqkv, wqkv, 3 * DM, DM, 64, 32, CU_TENSOR_MAP_SWIZZLE_128B);
  make_map2d(enc, &tm_o, p_o, DM, SEQ, 64, 64, CU_TENSOR_MAP_SWIZZLE_128B);
  make_map2d(enc, &tm_x, x, DM, SEQ, 72, 128, CU_TENSOR_MAP_SWIZZLE_NONE);
  make_map2d(enc, &tm_wmod, wmod, 6 * DM, DM, 192, 64, CU_TENSOR_MAP_SWIZZLE_NONE);
  make_map2d(enc, &tm_x2s, out, DM, SEQ, 72, 128, CU_TENSOR_MAP_SWIZZLE_NONE);
  make_map2d(enc, &tm_out, out, DM, SEQ, 72, 64, CU_TENSOR_MAP_SWIZZLE_NONE);
  make_map2d(enc, &tm_h2s, p_h2, DM, SEQ, 72, 128, CU_TENSOR_MAP_SWIZZLE_NONE);
  make_map2d(enc, &tm_wo, p_woT, DM, DM, 64, 72, CU_TENSOR_MAP_SWIZZLE_128B);
  make_map2d(enc, &tm_h2, p_h2, DM, SEQ, 64, 128, CU_TENSOR_MAP_SWIZZLE_128B);
  make_map2d(enc, &tm_w1, w1, FF, DM, 64, K4_BK / 2, CU_TENSOR_MAP_SWIZZLE_128B);
  make_map2d(enc, &tm_H, p_H, FF, SEQ, 64, 128, CU_TENSOR_MAP_SWIZZLE_128B);
  for (int narrow = 0; narrow < 2; narrow++) {
    cuuint64_t dims[5] = {(cuuint64_t)DM, 2, 4, 4, (cuuint64_t)(FF / 32)};
    cuuint64_t strides[4] = {(cuuint64_t)DM * 2, (cuuint64_t)DM * 2 * 8, (cuuint64_t)DM * 2 * 2, (cuuint64_t)DM * 2 * 32};
    cuuint32_t box[5] = {narrow ? 32u : 64u, 2, 4, 4, 2};
    cuuint32_t es[5] = {1, 1, 1, 1, 1};
    enc(narrow ? &tm_w2n : &tm_w2, CU_TENSOR_MAP_DATA_TYPE_BFLOAT16, 5, const_cast<bf16*>(w2), dims, strides, box, es, CU_TENSOR_MAP_INTERLEAVE_NONE,
        narrow ? CU_TENSOR_MAP_SWIZZLE_64B : CU_TENSOR_MAP_SWIZZLE_128B, CU_TENSOR_MAP_L2_PROMOTION_L2_128B, CU_TENSOR_MAP_FLOAT_OOB_FILL_NONE);
  }
  launch(k0_mod_ln, 36 * MODP + 128, 256, 0, false, 1, x, c, wmod, wqkv);
  launch(k1_qkv, 128, 352, K1_SMEM, USE_PDL, 2, tm_xn, tm_wqkv, wo);
  launch(k2_attn, 132, 512, K2_SMEM, USE_PDL, 1, tm_wmod, c, w1, w2);
  launch(k3_wo, 128, 320, K3_SMEM, USE_PDL, 2, tm_o, tm_wo, tm_x, tm_x2s, tm_h2s);
  launch(k4_mlp1, 128, 384, K4_SMEM, USE_PDL, 2, tm_h2, tm_w1, w2);
  launch(k5_mlp2, 128, 384, K5_SMEM, USE_PDL, 2, tm_H, tm_w2, tm_w2n, tm_out);
}
```

```cpp
#include <cuda_runtime.h>
#include <cuda_bf16.h>
#include <cuda.h>
#include <stdint.h>

namespace {

constexpr int SEQ = 2048, DM = 576, DHEAD = 18, FF = 4608;
constexpr int SLOT_BYTES = SEQ * 48;

typedef __nv_bfloat16 bf16;

__device__ __align__(1024) bf16    g_mod[6 * DM];
#define MODP 2
__device__ __align__(1024) float   g_modp[MODP * 2 * DM];
constexpr int ACT_BYTES = SEQ * DM * 2;
__device__ __align__(1024) uint8_t g_arena[ACT_BYTES + SEQ * FF * 2];
#define g_qkvp (g_arena)
#define g_h2   (reinterpret_cast<bf16*>(g_arena))
#define g_xn   (reinterpret_cast<bf16*>(g_arena + 96 * SLOT_BYTES))
#define g_o    (reinterpret_cast<bf16*>(g_arena + 96 * SLOT_BYTES))
#define g_H    (reinterpret_cast<bf16*>(g_arena + ACT_BYTES))
__device__ __align__(1024) float   g_nrm[16 * 8 * 16];
__device__ __align__(1024) bf16    g_woT[DM * DM];
__device__ __align__(1024) uint4   g_stats[SEQ * 8];
__device__ unsigned int g_epoch;

__device__ __forceinline__ uint32_t s2u(const void* p) { return (uint32_t)__cvta_generic_to_shared(p); }
__device__ __forceinline__ void mbar_init(uint32_t b, uint32_t c) { asm volatile("mbarrier.init.shared::cta.b64 [%0], %1;" :: "r"(b), "r"(c) : "memory"); }
__device__ __forceinline__ void mbar_expect(uint32_t b, uint32_t bytes) { asm volatile("mbarrier.arrive.expect_tx.shared::cta.b64 _, [%0], %1;" :: "r"(b), "r"(bytes) : "memory"); }
__device__ __forceinline__ void mbar_arrive(uint32_t b) { asm volatile("mbarrier.arrive.shared::cta.b64 _, [%0];" :: "r"(b) : "memory"); }
__device__ __forceinline__ bool mbar_try(uint32_t b, uint32_t ph) {
  uint32_t ok;
  asm volatile("{\n.reg .pred p;\nmbarrier.try_wait.parity.shared::cta.b64 p, [%1], %2;\nselp.u32 %0, 1, 0, p;\n}" : "=r"(ok) : "r"(b), "r"(ph) : "memory");
  return ok != 0;
}
__device__ __forceinline__ void mbar_wait(uint32_t b, uint32_t ph) {
  if (!mbar_try(b, ph)) {
    for (int n = 0; n < (1 << 22); n++) if (mbar_try(b, ph)) break;
  }
}
__device__ __forceinline__ void fence_barrier_init() { asm volatile("fence.mbarrier_init.release.cluster;" ::: "memory"); }
__device__ __forceinline__ void fence_async_smem() { asm volatile("fence.proxy.async.shared::cta;" ::: "memory"); }
__device__ __forceinline__ void bar_sync(int id, int n) { asm volatile("bar.sync %0, %1;" :: "r"(id), "r"(n) : "memory"); }
__device__ __forceinline__ void pdl_wait() { asm volatile("griddepcontrol.wait;" ::: "memory"); }
__device__ __forceinline__ void pdl_launch() { asm volatile("griddepcontrol.launch_dependents;" ::: "memory"); }
__device__ __forceinline__ void bulk_g2s(uint32_t dst, const void* src, uint32_t bytes, uint32_t bar) {
  asm volatile("cp.async.bulk.shared::cluster.global.mbarrier::complete_tx::bytes [%0], [%1], %2, [%3];" :: "r"(dst), "l"(src), "r"(bytes), "r"(bar) : "memory");
}
__device__ __forceinline__ void bulk_s2g(void* dst, uint32_t src, uint32_t bytes) {
  asm volatile("cp.async.bulk.global.shared::cta.bulk_group [%0], [%1], %2;" :: "l"(dst), "r"(src), "r"(bytes) : "memory");
}
__device__ __forceinline__ void bulk_commit() { asm volatile("cp.async.bulk.commit_group;" ::: "memory"); }
__device__ __forceinline__ void bulk_wait_read() { asm volatile("cp.async.bulk.wait_group.read 0;" ::: "memory"); }
__device__ __forceinline__ void tma2d(uint32_t dst, const CUtensorMap* m, int x, int y, uint32_t bar) {
  asm volatile("cp.async.bulk.tensor.2d.shared::cluster.global.mbarrier::complete_tx::bytes [%0], [%1, {%3, %4}], [%2];"
               :: "r"(dst), "l"(m), "r"(bar), "r"(x), "r"(y) : "memory");
}
__device__ __forceinline__ void tma2d_mc(uint32_t dst, const CUtensorMap* m, int x, int y, uint32_t bar) {
  asm volatile("cp.async.bulk.tensor.2d.shared::cluster.global.mbarrier::complete_tx::bytes.multicast::cluster [%0], [%1, {%3, %4}], [%2], %5;"
               :: "r"(dst), "l"(m), "r"(bar), "r"(x), "r"(y), "h"((uint16_t)3) : "memory");
}
__device__ __forceinline__ void tma5d_mc(uint32_t dst, const CUtensorMap* m, int c0, int c1, int c2, int c3, int c4, uint32_t bar) {
  asm volatile("cp.async.bulk.tensor.5d.shared::cluster.global.mbarrier::complete_tx::bytes.multicast::cluster [%0], [%1, {%3, %4, %5, %6, %7}], [%2], %8;"
               :: "r"(dst), "l"(m), "r"(bar), "r"(c0), "r"(c1), "r"(c2), "r"(c3), "r"(c4), "h"((uint16_t)3) : "memory");
}
__device__ __forceinline__ void tma2d_store(const CUtensorMap* m, uint32_t src, int x, int y) {
  asm volatile("cp.async.bulk.tensor.2d.global.shared::cta.bulk_group [%0, {%2, %3}], [%1];" :: "l"(m), "r"(src), "r"(x), "r"(y) : "memory");
}
__device__ __forceinline__ uint32_t map_cta(uint32_t a, uint32_t cta) { uint32_t r; asm("mapa.shared::cluster.u32 %0, %1, %2;" : "=r"(r) : "r"(a), "r"(cta)); return r; }
__device__ __forceinline__ void mbar_arrive_remote(uint32_t ra) { asm volatile("mbarrier.arrive.shared::cluster.b64 _, [%0];" :: "r"(ra) : "memory"); }
__device__ __forceinline__ void cluster_arrive_relaxed() { asm volatile("barrier.cluster.arrive.relaxed;" ::: "memory"); }
__device__ __forceinline__ void cluster_wait() { asm volatile("barrier.cluster.wait.acquire;" ::: "memory"); }
__device__ __forceinline__ uint32_t cluster_rank() { uint32_t r; asm("mov.u32 %0, %%cluster_ctarank;" : "=r"(r)); return r; }
__device__ __forceinline__ void tmap_prefetch(const CUtensorMap* m) { asm volatile("prefetch.tensormap [%0];" :: "l"(m) : "memory"); }
__device__ __forceinline__ void wg_fence() { asm volatile("wgmma.fence.sync.aligned;" ::: "memory"); }
__device__ __forceinline__ void wg_commit() { asm volatile("wgmma.commit_group.sync.aligned;" ::: "memory"); }
template <int N> __device__ __forceinline__ void wg_wait() { asm volatile("wgmma.wait_group.sync.aligned %0;" :: "n"(N) : "memory"); }
__device__ __forceinline__ uint64_t mkdesc(uint32_t addr, uint32_t lbo, uint32_t sbo, int sw) {
  return (uint64_t)((addr & 0x3FFFF) >> 4) | ((uint64_t)(lbo >> 4) << 16) | ((uint64_t)(sbo >> 4) << 32) | ((uint64_t)sw << 62);
}
template <int N> __device__ __forceinline__ void fence_regs(float (&d)[N]) {
#pragma unroll
  for (int i = 0; i < N; i++) asm volatile("" : "+f"(d[i]) :: "memory");
}
template <int N> __device__ __forceinline__ void fence_regs(uint32_t (&d)[N]) {
#pragma unroll
  for (int i = 0; i < N; i++) asm volatile("" : "+r"(d[i]) :: "memory");
}
__device__ __forceinline__ float ex2(float x) { float y; asm("ex2.approx.ftz.f32 %0, %1;" : "=f"(y) : "f"(x)); return y; }
__device__ __forceinline__ float tanh_fast(float x) { float y; asm("tanh.approx.f32 %0, %1;" : "=f"(y) : "f"(x)); return y; }
__device__ __forceinline__ uint32_t pack_bf16(float lo, float hi) { uint32_t v; asm("cvt.rn.bf16x2.f32 %0, %1, %2;" : "=r"(v) : "f"(hi), "f"(lo)); return v; }
__device__ __forceinline__ float bf_lo(uint32_t v) { return __uint_as_float(v << 16); }
__device__ __forceinline__ float bf_hi(uint32_t v) { return __uint_as_float(v & 0xFFFF0000u); }
__device__ __forceinline__ float bf_round(float x) { return __bfloat162float(__float2bfloat16_rn(x)); }
__device__ __forceinline__ uint32_t hfma2(uint32_t a, uint32_t b, uint32_t c) { uint32_t d; asm("fma.rn.bf16x2 %0, %1, %2, %3;" : "=r"(d) : "r"(a), "r"(b), "r"(c)); return d; }
__device__ __forceinline__ uint32_t hadd2(uint32_t a, uint32_t b) { uint32_t d; asm("add.rn.bf16x2 %0, %1, %2;" : "=r"(d) : "r"(a), "r"(b)); return d; }
__device__ __forceinline__ uint32_t opaque(uint32_t v) { uint32_t r; asm volatile("mov.b32 %0, %1;" : "=r"(r) : "r"(v)); return r; }
__device__ __forceinline__ void ldsm4(uint32_t (&r)[4], uint32_t a) {
  asm volatile("ldmatrix.sync.aligned.m8n8.x4.shared.b16 {%0,%1,%2,%3}, [%4];" : "=r"(r[0]), "=r"(r[1]), "=r"(r[2]), "=r"(r[3]) : "r"(a));
}
__device__ __forceinline__ uint4 lds128(uint32_t a) { uint4 v; asm volatile("ld.shared.v4.b32 {%0,%1,%2,%3}, [%4];" : "=r"(v.x), "=r"(v.y), "=r"(v.z), "=r"(v.w) : "r"(a)); return v; }
__device__ __forceinline__ uint32_t lds32(uint32_t a) { uint32_t v; asm volatile("ld.shared.b32 %0, [%1];" : "=r"(v) : "r"(a)); return v; }
__device__ __forceinline__ void sts32(uint32_t a, uint32_t v) { asm volatile("st.shared.b32 [%0], %1;" :: "r"(a), "r"(v) : "memory"); }
template <int R> __device__ __forceinline__ void reg_inc() { asm volatile("setmaxnreg.inc.sync.aligned.u32 %0;" :: "n"(R)); }
template <int R> __device__ __forceinline__ void reg_dec() { asm volatile("setmaxnreg.dec.sync.aligned.u32 %0;" :: "n"(R)); }

#define TL(k, i)
#define TLT(k, i, t)
#define TLC(k, i, t)

__device__ __forceinline__ void wgmma_rs_n216_tb(float (&d)[108], uint32_t a0, uint32_t a1, uint32_t a2, uint32_t a3, uint64_t db, int sd) {
  asm volatile("{\n.reg .pred p;\nsetp.ne.b32 p, %113, 0;\n"
    "wgmma.mma_async.sync.aligned.m64n216k16.f32.bf16.bf16 "
    "{%0, %1, %2, %3, %4, %5, %6, %7, %8, %9, %10, %11, %12, %13, %14, %15, %16, %17, %18, %19, %20, %21, %22, %23, %24, %25, %26, %27, %28, %29, %30, %31, %32, %33, %34, %35, %36, %37, %38, %39, %40, %41, %42, %43, %44, %45, %46, %47, %48, %49, %50, %51, %52, %53, %54, %55, %56, %57, %58, %59, %60, %61, %62, %63, %64, %65, %66, %67, %68, %69, %70, %71, %72, %73, %74, %75, %76, %77, %78, %79, %80, %81, %82, %83, %84, %85, %86, %87, %88, %89, %90, %91, %92, %93, %94, %95, %96, %97, %98, %99, %100, %101, %102, %103, %104, %105, %106, %107}, {%108,%109,%110,%111}, %112, p, 1, 1, 1;\n}\n"
    : "+f"(d[0]), "+f"(d[1]), "+f"(d[2]), "+f"(d[3]), "+f"(d[4]), "+f"(d[5]), "+f"(d[6]), "+f"(d[7]), "+f"(d[8]), "+f"(d[9]), "+f"(d[10]), "+f"(d[11]), "+f"(d[12]), "+f"(d[13]), "+f"(d[14]), "+f"(d[15]), "+f"(d[16]), "+f"(d[17]), "+f"(d[18]), "+f"(d[19]), "+f"(d[20]), "+f"(d[21]), "+f"(d[22]), "+f"(d[23]), "+f"(d[24]), "+f"(d[25]), "+f"(d[26]), "+f"(d[27]), "+f"(d[28]), "+f"(d[29]), "+f"(d[30]), "+f"(d[31]), "+f"(d[32]), "+f"(d[33]), "+f"(d[34]), "+f"(d[35]), "+f"(d[36]), "+f"(d[37]), "+f"(d[38]), "+f"(d[39]), "+f"(d[40]), "+f"(d[41]), "+f"(d[42]), "+f"(d[43]), "+f"(d[44]), "+f"(d[45]), "+f"(d[46]), "+f"(d[47]), "+f"(d[48]), "+f"(d[49]), "+f"(d[50]), "+f"(d[51]), "+f"(d[52]), "+f"(d[53]), "+f"(d[54]), "+f"(d[55]), "+f"(d[56]), "+f"(d[57]), "+f"(d[58]), "+f"(d[59]), "+f"(d[60]), "+f"(d[61]), "+f"(d[62]), "+f"(d[63]), "+f"(d[64]), "+f"(d[65]), "+f"(d[66]), "+f"(d[67]), "+f"(d[68]), "+f"(d[69]), "+f"(d[70]), "+f"(d[71]), "+f"(d[72]), "+f"(d[73]), "+f"(d[74]), "+f"(d[75]), "+f"(d[76]), "+f"(d[77]), "+f"(d[78]), "+f"(d[79]), "+f"(d[80]), "+f"(d[81]), "+f"(d[82]), "+f"(d[83]), "+f"(d[84]), "+f"(d[85]), "+f"(d[86]), "+f"(d[87]), "+f"(d[88]), "+f"(d[89]), "+f"(d[90]), "+f"(d[91]), "+f"(d[92]), "+f"(d[93]), "+f"(d[94]), "+f"(d[95]), "+f"(d[96]), "+f"(d[97]), "+f"(d[98]), "+f"(d[99]), "+f"(d[100]), "+f"(d[101]), "+f"(d[102]), "+f"(d[103]), "+f"(d[104]), "+f"(d[105]), "+f"(d[106]), "+f"(d[107])
    : "r"(a0), "r"(a1), "r"(a2), "r"(a3), "l"(db), "r"(sd));
}
__device__ __forceinline__ void wgmma_ss_n72(float (&d)[36], uint64_t da, uint64_t db, int sd) {
  asm volatile("{\n.reg .pred p;\nsetp.ne.b32 p, %38, 0;\n"
    "wgmma.mma_async.sync.aligned.m64n72k16.f32.bf16.bf16 "
    "{%0, %1, %2, %3, %4, %5, %6, %7, %8, %9, %10, %11, %12, %13, %14, %15, %16, %17, %18, %19, %20, %21, %22, %23, %24, %25, %26, %27, %28, %29, %30, %31, %32, %33, %34, %35}, %36, %37, p, 1, 1, 0, 0;\n}\n"
    : "+f"(d[0]), "+f"(d[1]), "+f"(d[2]), "+f"(d[3]), "+f"(d[4]), "+f"(d[5]), "+f"(d[6]), "+f"(d[7]), "+f"(d[8]), "+f"(d[9]), "+f"(d[10]), "+f"(d[11]), "+f"(d[12]), "+f"(d[13]), "+f"(d[14]), "+f"(d[15]), "+f"(d[16]), "+f"(d[17]), "+f"(d[18]), "+f"(d[19]), "+f"(d[20]), "+f"(d[21]), "+f"(d[22]), "+f"(d[23]), "+f"(d[24]), "+f"(d[25]), "+f"(d[26]), "+f"(d[27]), "+f"(d[28]), "+f"(d[29]), "+f"(d[30]), "+f"(d[31]), "+f"(d[32]), "+f"(d[33]), "+f"(d[34]), "+f"(d[35])
    : "l"(da), "l"(db), "r"(sd));
}
__device__ __forceinline__ void wgmma_ss_n192_tb(float (&d)[96], uint64_t da, uint64_t db, int sd) {
  asm volatile("{\n.reg .pred p;\nsetp.ne.b32 p, %98, 0;\n"
    "wgmma.mma_async.sync.aligned.m64n192k16.f32.bf16.bf16 "
    "{%0, %1, %2, %3, %4, %5, %6, %7, %8, %9, %10, %11, %12, %13, %14, %15, %16, %17, %18, %19, %20, %21, %22, %23, %24, %25, %26, %27, %28, %29, %30, %31, %32, %33, %34, %35, %36, %37, %38, %39, %40, %41, %42, %43, %44, %45, %46, %47, %48, %49, %50, %51, %52, %53, %54, %55, %56, %57, %58, %59, %60, %61, %62, %63, %64, %65, %66, %67, %68, %69, %70, %71, %72, %73, %74, %75, %76, %77, %78, %79, %80, %81, %82, %83, %84, %85, %86, %87, %88, %89, %90, %91, %92, %93, %94, %95}, %96, %97, p, 1, 1, 0, 1;\n}\n"
    : "+f"(d[0]), "+f"(d[1]), "+f"(d[2]), "+f"(d[3]), "+f"(d[4]), "+f"(d[5]), "+f"(d[6]), "+f"(d[7]), "+f"(d[8]), "+f"(d[9]), "+f"(d[10]), "+f"(d[11]), "+f"(d[12]), "+f"(d[13]), "+f"(d[14]), "+f"(d[15]), "+f"(d[16]), "+f"(d[17]), "+f"(d[18]), "+f"(d[19]), "+f"(d[20]), "+f"(d[21]), "+f"(d[22]), "+f"(d[23]), "+f"(d[24]), "+f"(d[25]), "+f"(d[26]), "+f"(d[27]), "+f"(d[28]), "+f"(d[29]), "+f"(d[30]), "+f"(d[31]), "+f"(d[32]), "+f"(d[33]), "+f"(d[34]), "+f"(d[35]), "+f"(d[36]), "+f"(d[37]), "+f"(d[38]), "+f"(d[39]), "+f"(d[40]), "+f"(d[41]), "+f"(d[42]), "+f"(d[43]), "+f"(d[44]), "+f"(d[45]), "+f"(d[46]), "+f"(d[47]), "+f"(d[48]), "+f"(d[49]), "+f"(d[50]), "+f"(d[51]), "+f"(d[52]), "+f"(d[53]), "+f"(d[54]), "+f"(d[55]), "+f"(d[56]), "+f"(d[57]), "+f"(d[58]), "+f"(d[59]), "+f"(d[60]), "+f"(d[61]), "+f"(d[62]), "+f"(d[63]), "+f"(d[64]), "+f"(d[65]), "+f"(d[66]), "+f"(d[67]), "+f"(d[68]), "+f"(d[69]), "+f"(d[70]), "+f"(d[71]), "+f"(d[72]), "+f"(d[73]), "+f"(d[74]), "+f"(d[75]), "+f"(d[76]), "+f"(d[77]), "+f"(d[78]), "+f"(d[79]), "+f"(d[80]), "+f"(d[81]), "+f"(d[82]), "+f"(d[83]), "+f"(d[84]), "+f"(d[85]), "+f"(d[86]), "+f"(d[87]), "+f"(d[88]), "+f"(d[89]), "+f"(d[90]), "+f"(d[91]), "+f"(d[92]), "+f"(d[93]), "+f"(d[94]), "+f"(d[95])
    : "l"(da), "l"(db), "r"(sd));
}
__device__ __forceinline__ void wgmma_rs_n256_tb(float (&d)[128], uint32_t a0, uint32_t a1, uint32_t a2, uint32_t a3, uint64_t db, int sd) {
  asm volatile("{\n.reg .pred p;\nsetp.ne.b32 p, %133, 0;\n"
    "wgmma.mma_async.sync.aligned.m64n256k16.f32.bf16.bf16 "
    "{%0, %1, %2, %3, %4, %5, %6, %7, %8, %9, %10, %11, %12, %13, %14, %15, %16, %17, %18, %19, %20, %21, %22, %23, %24, %25, %26, %27, %28, %29, %30, %31, %32, %33, %34, %35, %36, %37, %38, %39, %40, %41, %42, %43, %44, %45, %46, %47, %48, %49, %50, %51, %52, %53, %54, %55, %56, %57, %58, %59, %60, %61, %62, %63, %64, %65, %66, %67, %68, %69, %70, %71, %72, %73, %74, %75, %76, %77, %78, %79, %80, %81, %82, %83, %84, %85, %86, %87, %88, %89, %90, %91, %92, %93, %94, %95, %96, %97, %98, %99, %100, %101, %102, %103, %104, %105, %106, %107, %108, %109, %110, %111, %112, %113, %114, %115, %116, %117, %118, %119, %120, %121, %122, %123, %124, %125, %126, %127}, {%128,%129,%130,%131}, %132, p, 1, 1, 1;\n}\n"
    : "+f"(d[0]), "+f"(d[1]), "+f"(d[2]), "+f"(d[3]), "+f"(d[4]), "+f"(d[5]), "+f"(d[6]), "+f"(d[7]), "+f"(d[8]), "+f"(d[9]), "+f"(d[10]), "+f"(d[11]), "+f"(d[12]), "+f"(d[13]), "+f"(d[14]), "+f"(d[15]), "+f"(d[16]), "+f"(d[17]), "+f"(d[18]), "+f"(d[19]), "+f"(d[20]), "+f"(d[21]), "+f"(d[22]), "+f"(d[23]), "+f"(d[24]), "+f"(d[25]), "+f"(d[26]), "+f"(d[27]), "+f"(d[28]), "+f"(d[29]), "+f"(d[30]), "+f"(d[31]), "+f"(d[32]), "+f"(d[33]), "+f"(d[34]), "+f"(d[35]), "+f"(d[36]), "+f"(d[37]), "+f"(d[38]), "+f"(d[39]), "+f"(d[40]), "+f"(d[41]), "+f"(d[42]), "+f"(d[43]), "+f"(d[44]), "+f"(d[45]), "+f"(d[46]), "+f"(d[47]), "+f"(d[48]), "+f"(d[49]), "+f"(d[50]), "+f"(d[51]), "+f"(d[52]), "+f"(d[53]), "+f"(d[54]), "+f"(d[55]), "+f"(d[56]), "+f"(d[57]), "+f"(d[58]), "+f"(d[59]), "+f"(d[60]), "+f"(d[61]), "+f"(d[62]), "+f"(d[63]), "+f"(d[64]), "+f"(d[65]), "+f"(d[66]), "+f"(d[67]), "+f"(d[68]), "+f"(d[69]), "+f"(d[70]), "+f"(d[71]), "+f"(d[72]), "+f"(d[73]), "+f"(d[74]), "+f"(d[75]), "+f"(d[76]), "+f"(d[77]), "+f"(d[78]), "+f"(d[79]), "+f"(d[80]), "+f"(d[81]), "+f"(d[82]), "+f"(d[83]), "+f"(d[84]), "+f"(d[85]), "+f"(d[86]), "+f"(d[87]), "+f"(d[88]), "+f"(d[89]), "+f"(d[90]), "+f"(d[91]), "+f"(d[92]), "+f"(d[93]), "+f"(d[94]), "+f"(d[95]), "+f"(d[96]), "+f"(d[97]), "+f"(d[98]), "+f"(d[99]), "+f"(d[100]), "+f"(d[101]), "+f"(d[102]), "+f"(d[103]), "+f"(d[104]), "+f"(d[105]), "+f"(d[106]), "+f"(d[107]), "+f"(d[108]), "+f"(d[109]), "+f"(d[110]), "+f"(d[111]), "+f"(d[112]), "+f"(d[113]), "+f"(d[114]), "+f"(d[115]), "+f"(d[116]), "+f"(d[117]), "+f"(d[118]), "+f"(d[119]), "+f"(d[120]), "+f"(d[121]), "+f"(d[122]), "+f"(d[123]), "+f"(d[124]), "+f"(d[125]), "+f"(d[126]), "+f"(d[127])
    : "r"(a0), "r"(a1), "r"(a2), "r"(a3), "l"(db), "r"(sd));
}
__device__ __forceinline__ void wgmma_rs_n32_tb(float (&d)[16], uint32_t a0, uint32_t a1, uint32_t a2, uint32_t a3, uint64_t db, int sd) {
  asm volatile("{\n.reg .pred p;\nsetp.ne.b32 p, %21, 0;\n"
    "wgmma.mma_async.sync.aligned.m64n32k16.f32.bf16.bf16 "
    "{%0, %1, %2, %3, %4, %5, %6, %7, %8, %9, %10, %11, %12, %13, %14, %15}, {%16,%17,%18,%19}, %20, p, 1, 1, 1;\n}\n"
    : "+f"(d[0]), "+f"(d[1]), "+f"(d[2]), "+f"(d[3]), "+f"(d[4]), "+f"(d[5]), "+f"(d[6]), "+f"(d[7]), "+f"(d[8]), "+f"(d[9]), "+f"(d[10]), "+f"(d[11]), "+f"(d[12]), "+f"(d[13]), "+f"(d[14]), "+f"(d[15])
    : "r"(a0), "r"(a1), "r"(a2), "r"(a3), "l"(db), "r"(sd));
}
__device__ __forceinline__ void wgmma_rs_n64(float (&d)[32], uint32_t a0, uint32_t a1, uint32_t a2, uint32_t a3, uint64_t db, int sd) {
  asm volatile("{\n.reg .pred p;\nsetp.ne.b32 p, %37, 0;\n"
    "wgmma.mma_async.sync.aligned.m64n64k16.f32.bf16.bf16 "
    "{%0, %1, %2, %3, %4, %5, %6, %7, %8, %9, %10, %11, %12, %13, %14, %15, %16, %17, %18, %19, %20, %21, %22, %23, %24, %25, %26, %27, %28, %29, %30, %31}, {%32,%33,%34,%35}, %36, p, 1, 1, 0;\n}\n"
    : "+f"(d[0]), "+f"(d[1]), "+f"(d[2]), "+f"(d[3]), "+f"(d[4]), "+f"(d[5]), "+f"(d[6]), "+f"(d[7]), "+f"(d[8]), "+f"(d[9]), "+f"(d[10]), "+f"(d[11]), "+f"(d[12]), "+f"(d[13]), "+f"(d[14]), "+f"(d[15]), "+f"(d[16]), "+f"(d[17]), "+f"(d[18]), "+f"(d[19]), "+f"(d[20]), "+f"(d[21]), "+f"(d[22]), "+f"(d[23]), "+f"(d[24]), "+f"(d[25]), "+f"(d[26]), "+f"(d[27]), "+f"(d[28]), "+f"(d[29]), "+f"(d[30]), "+f"(d[31])
    : "r"(a0), "r"(a1), "r"(a2), "r"(a3), "l"(db), "r"(sd));
}
__device__ __forceinline__ void wgmma_rs0_n64(float (&d)[32], uint32_t a0, uint32_t a1, uint32_t a2, uint32_t a3, uint64_t db) {
  asm volatile("{\n.reg .pred p;\nsetp.ne.b32 p, 0, 0;\n"
    "wgmma.mma_async.sync.aligned.m64n64k16.f32.bf16.bf16 "
    "{%0, %1, %2, %3, %4, %5, %6, %7, %8, %9, %10, %11, %12, %13, %14, %15, %16, %17, %18, %19, %20, %21, %22, %23, %24, %25, %26, %27, %28, %29, %30, %31}, {%32,%33,%34,%35}, %36, p, 1, 1, 0;\n}\n"
    : "=f"(d[0]), "=f"(d[1]), "=f"(d[2]), "=f"(d[3]), "=f"(d[4]), "=f"(d[5]), "=f"(d[6]), "=f"(d[7]), "=f"(d[8]), "=f"(d[9]), "=f"(d[10]), "=f"(d[11]), "=f"(d[12]), "=f"(d[13]), "=f"(d[14]), "=f"(d[15]), "=f"(d[16]), "=f"(d[17]), "=f"(d[18]), "=f"(d[19]), "=f"(d[20]), "=f"(d[21]), "=f"(d[22]), "=f"(d[23]), "=f"(d[24]), "=f"(d[25]), "=f"(d[26]), "=f"(d[27]), "=f"(d[28]), "=f"(d[29]), "=f"(d[30]), "=f"(d[31])
    : "r"(a0), "r"(a1), "r"(a2), "r"(a3), "l"(db));
}
__device__ __forceinline__ void wgmma_rs_n24_tb(float (&d)[12], uint32_t a0, uint32_t a1, uint32_t a2, uint32_t a3, uint64_t db, int sd) {
  asm volatile("{\n.reg .pred p;\nsetp.ne.b32 p, %17, 0;\n"
    "wgmma.mma_async.sync.aligned.m64n24k16.f32.bf16.bf16 "
    "{%0, %1, %2, %3, %4, %5, %6, %7, %8, %9, %10, %11}, {%12,%13,%14,%15}, %16, p, 1, 1, 1;\n}\n"
    : "+f"(d[0]), "+f"(d[1]), "+f"(d[2]), "+f"(d[3]), "+f"(d[4]), "+f"(d[5]), "+f"(d[6]), "+f"(d[7]), "+f"(d[8]), "+f"(d[9]), "+f"(d[10]), "+f"(d[11])
    : "r"(a0), "r"(a1), "r"(a2), "r"(a3), "l"(db), "r"(sd));
}

__device__ __forceinline__ float silu_ref(float c) { return bf_round(c / (1.0f + __expf(-c))); }

__global__ void __launch_bounds__(256) k0_mod_ln(const bf16* __restrict__ x, const bf16* __restrict__ c, const bf16* __restrict__ wmod,
                                                 const bf16* __restrict__ wqkv) {
  __shared__ float red[8][32];
  pdl_launch();
  const int t = threadIdx.x, warp = t >> 5, lane = t & 31;
  if (blockIdx.x < 36 * MODP) {
    constexpr int ROWS = DM / MODP, NJ = (ROWS + 63) / 64;
    const int b = blockIdx.x, strip = b % 36, half = b / 36, cq = t & 3, kr = t >> 2;
    if (b == 0 && t == 0) g_epoch = g_epoch + 1;
    uint4 wv[NJ]; float cs[NJ];
#pragma unroll
    for (int j = 0; j < NJ; j++) {
      const int kk = kr + 64 * j, k = half * ROWS + kk;
      if (kk < ROWS) { wv[j] = __ldg(reinterpret_cast<const uint4*>(wmod + (size_t)k * (6 * DM) + strip * 32 + cq * 8)); cs[j] = __bfloat162float(c[k]); }
      else { wv[j] = make_uint4(0, 0, 0, 0); cs[j] = 0.f; }
    }
    float acc[8];
#pragma unroll
    for (int i = 0; i < 8; i++) acc[i] = 0.f;
#pragma unroll
    for (int j = 0; j < NJ; j++) {
      const float s = silu_ref(cs[j]);
      const uint32_t w[4] = {wv[j].x, wv[j].y, wv[j].z, wv[j].w};
#pragma unroll
      for (int i = 0; i < 4; i++) { acc[2 * i] = fmaf(s, bf_lo(w[i]), acc[2 * i]); acc[2 * i + 1] = fmaf(s, bf_hi(w[i]), acc[2 * i + 1]); }
    }
#pragma unroll
    for (int o = 4; o < 32; o <<= 1) {
#pragma unroll
      for (int i = 0; i < 8; i++) acc[i] += __shfl_xor_sync(0xffffffffu, acc[i], o);
    }
    if (lane < 4) {
#pragma unroll
      for (int i = 0; i < 8; i++) red[warp][lane * 8 + i] = acc[i];
    }
    __syncthreads();
    if (t < 32) {
      float s = 0.f;
#pragma unroll
      for (int w = 0; w < 8; w++) s += red[w][t];
      g_modp[half * 1152 + strip * 32 + t] = s;
    }
  } else {
    const int r0 = (blockIdx.x - 36 * MODP) * 16 + warp * 2;
    const uint32_t* xr = reinterpret_cast<const uint32_t*>(x + (size_t)r0 * DM);
    uint32_t xv[2][9];
#pragma unroll
    for (int j = 0; j < 9; j++) { xv[0][j] = __ldg(xr + lane + 32 * j); xv[1][j] = __ldg(xr + 288 + lane + 32 * j); }
    if (t == 0)
      asm volatile("cp.async.bulk.prefetch.L2.global [%0], %1;"
                   :: "l"(reinterpret_cast<const char*>(wqkv) + (size_t)(blockIdx.x - 36 * MODP) * (DM * 3 * DM * 2 / 128)), "r"(DM * 3 * DM * 2 / 128) : "memory");
    float s0 = 0.f, s1 = 0.f;
#pragma unroll
    for (int j = 0; j < 9; j++) { s0 += bf_lo(xv[0][j]) + bf_hi(xv[0][j]); s1 += bf_lo(xv[1][j]) + bf_hi(xv[1][j]); }
#pragma unroll
    for (int o = 16; o; o >>= 1) { s0 += __shfl_xor_sync(0xffffffffu, s0, o); s1 += __shfl_xor_sync(0xffffffffu, s1, o); }
    const float m0 = s0 * (1.0f / DM), m1 = s1 * (1.0f / DM);
    float v0 = 0.f, v1 = 0.f;
#pragma unroll
    for (int j = 0; j < 9; j++) {
      float d;
      d = bf_lo(xv[0][j]) - m0; v0 = fmaf(d, d, v0); d = bf_hi(xv[0][j]) - m0; v0 = fmaf(d, d, v0);
      d = bf_lo(xv[1][j]) - m1; v1 = fmaf(d, d, v1); d = bf_hi(xv[1][j]) - m1; v1 = fmaf(d, d, v1);
    }
#pragma unroll
    for (int o = 16; o; o >>= 1) { v0 += __shfl_xor_sync(0xffffffffu, v0, o); v1 += __shfl_xor_sync(0xffffffffu, v1, o); }
    const float rs0 = 1.0f / sqrtf(v0 * (1.0f / DM) + 1e-5f), rs1 = 1.0f / sqrtf(v1 * (1.0f / DM) + 1e-5f);
    uint32_t* o32 = reinterpret_cast<uint32_t*>(g_xn + (size_t)r0 * DM);
#pragma unroll
    for (int j = 0; j < 9; j++) {
      o32[lane + 32 * j] = pack_bf16((bf_lo(xv[0][j]) - m0) * rs0, (bf_hi(xv[0][j]) - m0) * rs0);
      o32[288 + lane + 32 * j] = pack_bf16((bf_lo(xv[1][j]) - m1) * rs1, (bf_hi(xv[1][j]) - m1) * rs1);
    }
  }
}

__device__ __forceinline__ void mod_tail(const bf16* __restrict__ c, const CUtensorMap* tm_wmod, int part, uint8_t* smem, uint32_t bar) {
  const int t = threadIdx.x;
  const uint32_t sb = s2u(smem);
  float* sc = reinterpret_cast<float*>(smem + 2 * 73728);
  float* red = sc + 576;
  auto fill = [&](int b) {
    mbar_expect(bar + 8 * (b & 1), 73728);
    for (int j = 0; j < 3; j++) tma2d(sb + (b & 1) * 73728 + j * 24576, tm_wmod, 1152 + part * 576 + j * 192, b * 64, bar + 8 * (b & 1));
  };
  if (t == 0) { fill(0); fill(1); }
  for (int k = t; k < DM; k += 512) sc[k] = silu_ref(__bfloat162float(c[k]));
  __syncthreads();
  const int cg = t % 72, rg = t / 72;
  float acc[8];
#pragma unroll
  for (int i = 0; i < 8; i++) acc[i] = 0.f;
#pragma unroll 1
  for (int b = 0; b < 9; b++) {
    mbar_wait(bar + 8 * (b & 1), (b >> 1) & 1);
    if (rg < 7) {
#pragma unroll 5
      for (int r = rg; r < 64; r += 7) {
        const uint4 v = lds128(sb + (b & 1) * 73728 + (cg / 24) * 24576 + r * 384 + (cg % 24) * 16);
        const float s = sc[b * 64 + r];
        acc[0] = fmaf(s, bf_lo(v.x), acc[0]); acc[1] = fmaf(s, bf_hi(v.x), acc[1]); acc[2] = fmaf(s, bf_lo(v.y), acc[2]); acc[3] = fmaf(s, bf_hi(v.y), acc[3]);
        acc[4] = fmaf(s, bf_lo(v.z), acc[4]); acc[5] = fmaf(s, bf_hi(v.z), acc[5]); acc[6] = fmaf(s, bf_lo(v.w), acc[6]); acc[7] = fmaf(s, bf_hi(v.w), acc[7]);
      }
    }
    __syncthreads();
    if (t == 0 && b + 2 < 9) fill(b + 2);
  }
  if (rg < 7) {
#pragma unroll
    for (int i = 0; i < 8; i++) red[rg * 576 + cg * 8 + i] = acc[i];
  }
  __syncthreads();
  for (int col = t; col < 576; col += 512) {
    float s = 0.f;
#pragma unroll
    for (int r = 0; r < 7; r++) s += red[r * 576 + col];
    g_mod[1152 + part * 576 + col] = __float2bfloat16_rn(s);
  }
}

constexpr int K1_NST = 5;
constexpr int K1_A = 0, K1_W = 147456, K1_MOD = K1_W + K1_NST * 16384, K1_RED = K1_MOD + 2304, K1_BAR = K1_RED + 256;
constexpr int K1_SMEM = K1_BAR + 8 * (10 + 2 * K1_NST);
#define QSCALE (0.23570226039551584f * 1.4426950408889634f)
#define POLY_MASK 0xFC
__host__ __device__ constexpr bool poly_block(int b) {
  return (POLY_MASK >> b) & 1;
}
constexpr uint32_t KPAD_POLY = 0x42FE47C0u;
constexpr uint32_t VPAD_ONE  = 0x00003F80u;

template <int ST>
__device__ __forceinline__ void k1_load_a(uint32_t (&A)[2][4], const uint32_t (&aoff)[4], uint32_t mtab) {
#pragma unroll
  for (int j = 0; j < 2; j++) {
    ldsm4(A[j], aoff[(ST & 1) * 2 + j] + (ST >> 1) * 16384);
    const uint4 m = lds128(mtab + (ST * 2 + j) * 64);
    A[j][0] = hfma2(A[j][0], m.x, m.z); A[j][1] = hfma2(A[j][1], m.x, m.z);
    A[j][2] = hfma2(A[j][2], m.y, m.w); A[j][3] = hfma2(A[j][3], m.y, m.w);
  }
}
template <int ST>
__device__ __forceinline__ void k1_steps(float (&acc)[108], uint32_t (&A)[3][2][4], const uint32_t (&aoff)[4], uint32_t mtab, uint64_t db0,
                                         uint32_t bx, uint32_t bwf, uint32_t rbe, bool releaser) {
  if constexpr (ST < 18) {
    constexpr int s = ST % K1_NST;
    mbar_wait(bwf + 8 * s, (ST / K1_NST) & 1);
    fence_regs(A[ST % 3][0]); fence_regs(A[ST % 3][1]);
    wg_fence();
#pragma unroll
    for (int j = 0; j < 2; j++)
      wgmma_rs_n216_tb(acc, A[ST % 3][j][0], A[ST % 3][j][1], A[ST % 3][j][2], A[ST % 3][j][3], db0 + (uint64_t)(s * 1024 + j * 128), 1);
    wg_commit();
    if constexpr (ST + 1 < 18) {
      if constexpr (((ST + 1) & 1) == 0) mbar_wait(bx + 8 * ((ST + 1) >> 1), 0);
      k1_load_a<ST + 1>(A[(ST + 1) % 3], aoff, mtab);
    }
    if constexpr (ST > 0) {
      wg_wait<1>();
      if (ST - 1 + K1_NST < 18 && releaser) mbar_arrive_remote(rbe + 8 * ((ST - 1) % K1_NST));
    }
    k1_steps<ST + 1>(acc, A, aoff, mtab, db0, bx, bwf, rbe, releaser);
  }
}

__host__ __device__ constexpr int k1_off(int I, int Q) {
  const int col = 8 * I + 2 * Q, sl = col / 18, d = col % 18;
  return sl * 6144 + (d >> 3) * 128 + (d & 7) * 2 - 4 * Q;
}
template <int I>
__device__ __forceinline__ void k1_stage_block(const float (&acc)[108], uint32_t base, int q4, int nq) {
  uint32_t a = base + k1_off(I, 0);
  if constexpr (k1_off(I, 1) != k1_off(I, 0)) a += q4 >= 1 ? k1_off(I, 1) - k1_off(I, 0) : 0;
  if constexpr (k1_off(I, 2) != k1_off(I, 1)) a += q4 >= 2 ? k1_off(I, 2) - k1_off(I, 1) : 0;
  if constexpr (k1_off(I, 3) != k1_off(I, 2)) a += q4 >= 3 ? k1_off(I, 3) - k1_off(I, 2) : 0;
  constexpr int s0 = (8 * I) / 18, s3 = (8 * I + 6) / 18, qs = s0 == s3 ? 4 : (18 * s3 - 8 * I) / 2;
  const float sc = ((q4 >= qs ? s3 : s0) < nq) ? QSCALE : 1.0f;
  sts32(a, pack_bf16(acc[4 * I] * sc, acc[4 * I + 1] * sc));
  sts32(a + 384, pack_bf16(acc[4 * I + 2] * sc, acc[4 * I + 3] * sc));
}
template <int G>
__device__ __forceinline__ void k1_stage_group(const float (&acc)[108], uint32_t base, uint32_t pbase, uint32_t kpad, int q4, int nt, int rb, int tid,
                                               uint32_t sb) {
  const int nq = 32 - 12 * nt;
  k1_stage_block<9 * G + 0>(acc, base, q4, nq); k1_stage_block<9 * G + 1>(acc, base, q4, nq); k1_stage_block<9 * G + 2>(acc, base, q4, nq);
  k1_stage_block<9 * G + 3>(acc, base, q4, nq); k1_stage_block<9 * G + 4>(acc, base, q4, nq); k1_stage_block<9 * G + 5>(acc, base, q4, nq);
  k1_stage_block<9 * G + 6>(acc, base, q4, nq); k1_stage_block<9 * G + 7>(acc, base, q4, nq); k1_stage_block<9 * G + 8>(acc, base, q4, nq);
#pragma unroll
  for (int i = 0; i < 2; i++) {
    const int slot = nt * 12 + 4 * G + 2 * i + (tid >> 7);
    const uint32_t pad = slot >= 64 ? VPAD_ONE : (slot >= 32 ? kpad : 0u);
    const uint32_t a = pbase + (4 * G + 2 * i) * 6144;
    sts32(a + 4, pad);
    asm volatile("st.shared.v2.b32 [%0], {%1, %1};" :: "r"(a + 8), "r"(0u) : "memory");
  }
  fence_async_smem();
  bar_sync(1, 256);
  if (tid == 0) {
#pragma unroll
    for (int sl = 4 * G; sl < 4 * G + 4; sl++)
      bulk_s2g(g_qkvp + (size_t)(nt * 12 + sl) * SLOT_BYTES + (size_t)rb * 6144, sb + sl * 6144, 6144);
    bulk_commit();
  }
}

__device__ __forceinline__ void transpose_wo_block(const bf16* __restrict__ wo, int kb, int nb, int lane) {
  const int h = lane & 1;
  uint4 v[2][8];
#pragma unroll
  for (int u = 0; u < 2; u++)
#pragma unroll
    for (int g = 0; g < 8; g++) v[u][g] = __ldg(reinterpret_cast<const uint4*>(wo + (size_t)(kb * 64 + u * 32 + lane) * DM + nb * 64 + g * 8));
  uint32_t* dst = reinterpret_cast<uint32_t*>(g_woT) + (size_t)(nb * 64 + 4 * h) * (DM / 2) + kb * 32 + (lane >> 1);
#pragma unroll
  for (int u = 0; u < 2; u++)
#pragma unroll
    for (int g = 0; g < 8; g++) {
      const uint32_t r0 = __shfl_xor_sync(0xffffffffu, h ? v[u][g].x : v[u][g].z, 1), r1 = __shfl_xor_sync(0xffffffffu, h ? v[u][g].y : v[u][g].w, 1);
      const uint32_t o0 = h ? v[u][g].z : v[u][g].x, o1 = h ? v[u][g].w : v[u][g].y;
      const uint32_t l0 = h ? r0 : o0, l1 = h ? r1 : o1, h0 = h ? o0 : r0, h1 = h ? o1 : r1;
      uint32_t* d = dst + (size_t)g * 8 * (DM / 2) + u * 16;
      d[0 * (DM / 2)] = __byte_perm(l0, h0, 0x5410); d[1 * (DM / 2)] = __byte_perm(l0, h0, 0x7632);
      d[2 * (DM / 2)] = __byte_perm(l1, h1, 0x5410); d[3 * (DM / 2)] = __byte_perm(l1, h1, 0x7632);
    }
}

__global__ void __launch_bounds__(352, 1) k1_qkv(const __grid_constant__ CUtensorMap tm_xn, const __grid_constant__ CUtensorMap tm_w, const bf16* __restrict__ wo) {
  extern __shared__ __align__(1024) uint8_t smem[];
  const uint32_t sb = s2u(smem);
  const int tid = threadIdx.x, nt = (blockIdx.x >> 1) & 7, rb = (blockIdx.x >> 4) * 2 + (blockIdx.x & 1);
  const uint32_t bx = sb + K1_BAR, bmp = bx + 72, bwf = bmp + 8, bwe = bwf + 8 * K1_NST;
  TL(1, 0);
  if (tid == 256) {
    for (int i = 0; i < 10; i++) mbar_init(bx + 8 * i, 1);
    for (int i = 0; i < K1_NST; i++) { mbar_init(bwf + 8 * i, 1); mbar_init(bwe + 8 * i, 4); }
    fence_barrier_init();
    tmap_prefetch(&tm_xn); tmap_prefetch(&tm_w);
  }
  __syncthreads();
  cluster_arrive_relaxed();
  pdl_launch();
  if (tid >= 320) {
    cluster_wait();
    if (blockIdx.x < 81) transpose_wo_block(wo, blockIdx.x / 9, blockIdx.x % 9, tid & 31);
    return;
  }
  if (tid >= 288) {
    auto load_x = [&](int c) { mbar_expect(bx + 8 * c, 16384); tma2d(sb + K1_A + c * 16384, &tm_xn, c * 64, rb * 128, bx + 8 * c); };
    if (tid == 288) {
      pdl_wait();
      mbar_expect(bmp, MODP * 2 * DM * 4); bulk_g2s(sb + K1_A + 8 * 16384, g_modp, MODP * 2 * DM * 4, bmp);
      load_x(0); load_x(1); load_x(2);
    }
    __syncwarp();
    cluster_wait();
    if (tid == 288)
      for (int c = 3; c < 9; c++) { mbar_wait(bx + 8 * (c - 3), 0); if (c == 8) mbar_wait(bwe, 0); load_x(c); }
    return;
  }
  if (tid >= 256) {
    cluster_wait();
    if (tid == 256) {
      const int rank = cluster_rank();
      auto load_w = [&](int st) {
        const int s = st % K1_NST;
        mbar_expect(bwf + 8 * s, 16384);
        for (int g = 2 * rank; g < 2 * rank + 2; g++) tma2d_mc(sb + K1_W + s * 16384 + g * 4096, &tm_w, nt * 216 + g * 64, st * 32, bwf + 8 * s);
      };
      for (int st = 0; st < K1_NST; st++) load_w(st);
      for (int st = K1_NST; st < 18; st++) {
        mbar_wait(bwe + 8 * (st % K1_NST), (st / K1_NST - 1) & 1);
        load_w(st);
      }
    }
    __syncwarp();
    cluster_arrive_relaxed(); cluster_wait();
    return;
  }
  cluster_wait();
  const int wg = __reduce_max_sync(0xffffffffu, (unsigned)tid >> 7), wtid = tid & 127, warp = (tid >> 5) & 3, lane = tid & 31, g = lane >> 2, q4 = lane & 3;
  const uint32_t rbe = map_cta(bwe, wtid & 1);
  TL(1, 1);
  {
    const float2* mp = reinterpret_cast<const float2*>(smem + K1_A + 8 * 16384);
    mbar_wait(bmp, 0);
    for (int i = tid; i < 288; i += 256) {
      float2 s0 = mp[i], c0 = mp[288 + i];
#pragma unroll
      for (int p = 1; p < MODP; p++) {
        const float2 s1 = mp[p * 576 + i], c1 = mp[p * 576 + 288 + i];
        s0.x += s1.x; s0.y += s1.y; c0.x += c1.x; c0.y += c1.y;
      }
      const uint32_t a = sb + K1_MOD + (i >> 3) * 64 + (i & 3) * 16 + ((i >> 2) & 1) * 4;
      sts32(a, hadd2(pack_bf16(c0.x, c0.y), 0x3F803F80u));
      sts32(a + 8, pack_bf16(s0.x, s0.y));
    }
  }
  bar_sync(1, 256);
  TL(1, 4);
  uint32_t aoff[4];
  {
    const int r = wg * 64 + warp * 16 + (lane & 7) + ((lane >> 3) & 1) * 8;
#pragma unroll
    for (int j = 0; j < 4; j++) aoff[j] = opaque(sb + K1_A + r * 128 + (((2 * j + (lane >> 4)) ^ (lane & 7)) << 4));
  }
  const uint32_t mtab = opaque(sb + K1_MOD + q4 * 16);
  float acc[108];
#pragma unroll
  for (int i = 0; i < 108; i++) acc[i] = 0.f;
  const uint64_t db0 = mkdesc(sb + K1_W, 4096, 1024, 1);
  uint32_t A[3][2][4];
  mbar_wait(bx, 0);
  TL(1, 5);
  k1_load_a<0>(A[0], aoff, mtab);
  k1_steps<0>(acc, A, aoff, mtab, db0, bx, bwf, rbe, wtid < 2);
  wg_wait<0>();
  fence_regs(acc);
  cluster_arrive_relaxed();
  TL(1, 2);
  bar_sync(1, 256);
  {
    const int tok = wg * 64 + warp * 16 + g;
    const uint32_t base = opaque(sb + (tok >> 3) * 384 + (tok & 7) * 16 + q4 * 4);
    const int tk = tid & 127;
    const uint32_t pbase = opaque(sb + (tid >> 7) * 6144 + (tk >> 3) * 384 + (tk & 7) * 16 + 256);
    const uint32_t kpad = poly_block((tk >> 3) & 7) ? KPAD_POLY : 0u;
    k1_stage_group<0>(acc, base, pbase, kpad, q4, nt, rb, tid, sb);
    k1_stage_group<1>(acc, base, pbase, kpad, q4, nt, rb, tid, sb);
    k1_stage_group<2>(acc, base, pbase, kpad, q4, nt, rb, tid, sb);
  }
  TL(1, 3);
  if (nt * 12 < 64) {
    const int tok = tid & 127;
    float* red = reinterpret_cast<float*>(smem + K1_RED);
#pragma unroll
    for (int i = 0; i < 6; i++) {
      const int sl = (tid >> 7) + 2 * i;
      const uint32_t a = sb + sl * 6144 + (tok >> 3) * 384 + (tok & 7) * 16;
      const uint4 v0 = lds128(a), v1 = lds128(a + 128);
      const uint32_t v2 = lds32(a + 256);
      float n2 = 0.f;
      const uint32_t w[9] = {v0.x, v0.y, v0.z, v0.w, v1.x, v1.y, v1.z, v1.w, v2};
#pragma unroll
      for (int j = 0; j < 9; j++) { n2 = fmaf(bf_lo(w[j]), bf_lo(w[j]), n2); n2 = fmaf(bf_hi(w[j]), bf_hi(w[j]), n2); }
      const uint32_t mx = __reduce_max_sync(0xffffffffu, __float_as_uint(n2) & 0x7FFFFFFFu);
      if (lane == 0) red[sl * 4 + warp] = __uint_as_float(mx);
    }
    bar_sync(1, 256);
    if (tid >= 32 && tid < 48) {
      const int sl = tid - 32;
      const uint32_t* r = reinterpret_cast<const uint32_t*>(red) + min(sl, 11) * 4;
      g_nrm[(rb * 8 + nt) * 16 + sl] = __uint_as_float(max(max(r[0], r[1]), max(r[2], r[3])));
    }
  }
  if (tid == 0) bulk_wait_read();
  TL(1, 7);
  cluster_wait();
}

constexpr int K2_K = 0, K2_V = SLOT_BYTES, K2_Q = 2 * SLOT_BYTES, K2_BAR = K2_Q + 512 * 48, K2_SMEM = K2_BAR + 8 * 19;
constexpr uint32_t EXP_C2 = 0x3EA93EA9u, EXP_C1 = 0x3B4E3B4Eu, EXP_C0 = 0x3F2C3F2Cu;
constexpr int K2_TD = 8 * 384 / 16;

__device__ __forceinline__ void attn_qk(float (&S)[32], const uint32_t (&q)[8], uint64_t kd) {
  wgmma_rs0_n64(S, q[0], q[1], q[2], q[3], kd);
  wgmma_rs_n64(S, q[4], q[5], q[6], q[7], kd + 16, 1);
}
__device__ __forceinline__ void attn_pv(float (&O)[12], const uint32_t (&P)[16], uint64_t vd) {
#pragma unroll
  for (int kk = 0; kk < 4; kk++) wgmma_rs_n24_tb(O, P[4 * kk], P[4 * kk + 1], P[4 * kk + 2], P[4 * kk + 3], vd + kk * 48, 1);
}
__device__ __forceinline__ void attn_exp(float (&S)[32], uint32_t c2, uint32_t cone) {
#pragma unroll
  for (int b = 0; b < 8; b++) {
    if (poly_block(b)) {
#pragma unroll
      for (int h = 0; h < 2; h++) {
        uint32_t w, y;
        asm("prmt.b32 %0, %1, %2, 0x5410;" : "=r"(w) : "r"(__float_as_uint(S[4 * b + 2 * h])), "r"(__float_as_uint(S[4 * b + 2 * h + 1])));
        asm("lop3.b32 %0, %1, 0x007F007F, %2, 0xEA;" : "=r"(y) : "r"(w), "r"(cone));
        const uint32_t p = hfma2(hfma2(y, c2, EXP_C1), y, EXP_C0);
        S[4 * b + 2 * h] = __uint_as_float(w);
        S[4 * b + 2 * h + 1] = __uint_as_float(p);
      }
    } else {
#pragma unroll
      for (int j = 0; j < 4; j++) S[4 * b + j] = ex2(S[4 * b + j]);
    }
  }
}
__device__ __forceinline__ void attn_pack(const float (&S)[32], uint32_t (&P)[16]) {
#pragma unroll
  for (int i = 0; i < 16; i++) {
    if (poly_block(i >> 1)) asm("lop3.b32 %0, %1, %2, 0xFF80FF80, 0xE4;" : "=r"(P[i]) : "r"(__float_as_uint(S[2 * i])), "r"(__float_as_uint(S[2 * i + 1])));
    else P[i] = pack_bf16(S[2 * i], S[2 * i + 1]);
  }
}

__device__ __forceinline__ void attn_load_chunk(uint32_t sb, uint32_t bar, const uint8_t* Kg, int c) {
  mbar_expect(bar + 8 * c, 2 * 6144);
  bulk_g2s(sb + K2_K + c * 6144, Kg + c * 6144, 6144, bar + 8 * c);
  bulk_g2s(sb + K2_V + c * 6144, Kg + (size_t)32 * SLOT_BYTES + c * 6144, 6144, bar + 8 * c);
}

template <bool WAIT>
__device__ __forceinline__ void attn_fast_pass(float (&O)[12], const uint32_t (&q)[8], uint64_t kd, uint64_t vd, uint32_t bar) {
  float S[32]; uint32_t P[16];
  const uint32_t c2 = opaque(EXP_C2), cone = opaque(0x3F803F80u);
  if (WAIT) mbar_wait(bar, 0);
  wg_fence();
  attn_qk(S, q, kd);
  wg_commit();
  wg_wait<0>();
  fence_regs(S);
  attn_exp(S, c2, cone);
  attn_pack(S, P);
  auto step = [&]() {
    kd += K2_TD;
    fence_regs(P); fence_regs(O);
    wg_fence();
    attn_qk(S, q, kd);
    wg_commit();
    attn_pv(O, P, vd);
    wg_commit();
    vd += K2_TD;
    wg_wait<1>();
    fence_regs(S);
    attn_exp(S, c2, cone);
    fence_regs(S);
    wg_wait<0>();
    fence_regs(S); fence_regs(O);
    attn_pack(S, P);
  };
#pragma unroll 1
  for (int c = 1; c < 16; c++) {
    if (WAIT) mbar_wait(bar + 8 * c, 0);
    step();
    step();
  }
  step();
  fence_regs(P); fence_regs(O);
  wg_fence();
  attn_pv(O, P, vd);
  wg_commit();
  wg_wait<0>();
  fence_regs(O);
}

__device__ __forceinline__ void attn_safe_pass(float (&O)[12], const uint32_t (&q)[8], uint64_t kd, uint64_t vd, uint32_t bar) {
  float S[32]; uint32_t P[16];
  float m0 = -INFINITY, m1 = -INFINITY;
  mbar_wait(bar, 0);
#pragma unroll 1
  for (int j = 0; j < 32; j++) {
    mbar_wait(bar + 8 * min((j + 1) >> 1, 15), 0);
    wg_fence();
    attn_qk(S, q, kd);
    wg_commit();
    wg_wait<0>();
    fence_regs(S);
    float x0 = m0, x1 = m1;
#pragma unroll
    for (int b = 0; b < 8; b++) { x0 = fmaxf(x0, fmaxf(S[4 * b], S[4 * b + 1])); x1 = fmaxf(x1, fmaxf(S[4 * b + 2], S[4 * b + 3])); }
    x0 = fmaxf(x0, __shfl_xor_sync(0xffffffffu, x0, 1)); x0 = fmaxf(x0, __shfl_xor_sync(0xffffffffu, x0, 2));
    x1 = fmaxf(x1, __shfl_xor_sync(0xffffffffu, x1, 1)); x1 = fmaxf(x1, __shfl_xor_sync(0xffffffffu, x1, 2));
    const float a0 = ex2(m0 - x0), a1 = ex2(m1 - x1);
    m0 = x0; m1 = x1;
#pragma unroll
    for (int b = 0; b < 3; b++) { O[4 * b] *= a0; O[4 * b + 1] *= a0; O[4 * b + 2] *= a1; O[4 * b + 3] *= a1; }
#pragma unroll
    for (int b = 0; b < 8; b++) {
      P[2 * b] = pack_bf16(ex2(S[4 * b] - m0), ex2(S[4 * b + 1] - m0));
      P[2 * b + 1] = pack_bf16(ex2(S[4 * b + 2] - m1), ex2(S[4 * b + 3] - m1));
    }
    fence_regs(P); fence_regs(O);
    wg_fence();
    attn_pv(O, P, vd);
    wg_commit();
    wg_wait<0>();
    fence_regs(O);
    kd += K2_TD; vd += K2_TD;
  }
}

__global__ void __launch_bounds__(512, 1) k2_attn(const __grid_constant__ CUtensorMap tm_wmod, const bf16* __restrict__ cvec,
                                                   const bf16* __restrict__ w1, const bf16* __restrict__ w2) {
  extern __shared__ __align__(1024) uint8_t smem[];
  const uint32_t sb = s2u(smem);
  const int head = blockIdx.x >> 2, qg = blockIdx.x & 3;
  const int tid = threadIdx.x, wg = __reduce_max_sync(0xffffffffu, (unsigned)tid >> 7), warp = (tid >> 5) & 3, lane = tid & 31, g = lane >> 2, q4 = lane & 3;
  const uint32_t bar = sb + K2_BAR;
  TL(2, 0);
  if (tid == 0) {
    for (int i = 0; i < 18; i++) mbar_init(bar + 8 * i, 1);
    fence_barrier_init();
  }
  __syncthreads();
  if (blockIdx.x >= 128) {
    mod_tail(cvec, &tm_wmod, blockIdx.x - 128, smem, bar);
    pdl_wait();
    return;
  }
  pdl_wait();
  pdl_launch();
  TL(2, 3);
  if ((tid >> 5) == 1) {
    uint32_t nv = 0;
    if (lane < 16) nv = __float_as_uint(__ldcg(&g_nrm[(lane * 8 + (32 + head) / 12) * 16 + (32 + head) % 12]));
    else if (lane < 20) nv = __float_as_uint(__ldcg(&g_nrm[((qg * 4 + lane - 16) * 8 + head / 12) * 16 + head % 12]));
    const uint32_t km = __reduce_max_sync(0xffffffffu, lane < 16 ? nv : 0u), qm = __reduce_max_sync(0xffffffffu, lane < 16 ? 0u : nv);
    if (lane == 0) sts32(bar + 8 * 18, __uint_as_float(km) * __uint_as_float(qm) <= 4096.0f ? 1u : 0u);
  }
  const uint8_t* Kg = g_qkvp + (size_t)(32 + head) * SLOT_BYTES;
  bool fast;
  {
    const uint8_t* Qg = g_qkvp + (size_t)head * SLOT_BYTES + (size_t)qg * 512 * 48;
    if (tid == 0) {
      mbar_expect(bar + 8 * 16, 4 * 3072);
      for (int w = 0; w < 4; w++) bulk_g2s(sb + K2_Q + w * 6144, Qg + w * 6144, 3072, bar + 8 * 16);
      for (int c = 0; c < 2; c++) attn_load_chunk(sb, bar, Kg, c);
    }
    __syncthreads();
    fast = lds32(bar + 8 * 18) != 0;
    if (tid == 32) {
      for (int c = 2; c < 16; c++) attn_load_chunk(sb, bar, Kg, c);
      mbar_expect(bar + 8 * 17, 4 * 3072);
      for (int w = 0; w < 4; w++) bulk_g2s(sb + K2_Q + w * 6144 + 3072, Qg + w * 6144 + 3072, 3072, bar + 8 * 17);
    }
    __syncwarp();
  }
  TL(2, 1);
  const uint64_t kd = mkdesc(sb + K2_K, 128, 384, 0);
  const uint64_t vd = mkdesc(sb + K2_V, 384, 128, 0);
#pragma unroll 1
  for (int it = 0; it < 2; it++) {
    const int qt = wg * 2 + it;
    mbar_wait(bar + 8 * (16 + it), 0);
    if (it == 0) TL(2, 4);
    uint32_t q[8];
    {
      const uint32_t base = sb + K2_Q + (qt * 8 + warp * 2) * 384 + g * 16 + q4 * 4;
#pragma unroll
      for (int j = 0; j < 3; j++) { q[2 * j] = lds32(base + j * 128); q[2 * j + 1] = lds32(base + 384 + j * 128); }
      if (fast && q4 == 1) { q[4] = 0x3F803F80u; q[5] = 0x3F803F80u; }
      q[6] = opaque(0u); q[7] = opaque(0u);
    }
    if (it == 1 && tid == 0) {
      const char* a = reinterpret_cast<const char*>(w1) + (size_t)blockIdx.x * (DM * FF * 2 / 128);
      const char* b = reinterpret_cast<const char*>(w2) + (size_t)blockIdx.x * (DM * FF * 2 / 128);
      asm volatile("cp.async.bulk.prefetch.L2.global [%0], %1;" :: "l"(a), "r"(DM * FF * 2 / 128) : "memory");
      asm volatile("cp.async.bulk.prefetch.L2.global [%0], %1;" :: "l"(b), "r"(DM * FF * 2 / 128) : "memory");
    }
    float O[12];
#pragma unroll
    for (int i = 0; i < 12; i++) O[i] = 0.f;
    if (fast) {
      if (it == 0) attn_fast_pass<true>(O, q, kd, vd, bar);
      else attn_fast_pass<false>(O, q, kd, vd, bar);
    } else {
      attn_safe_pass(O, q, kd, vd, bar);
    }
    const float l0 = __shfl_sync(0xffffffffu, O[8], (lane & ~3) | 1), l1 = __shfl_sync(0xffffffffu, O[10], (lane & ~3) | 1);
    const float r0 = __frcp_rn(l0), r1 = __frcp_rn(l1);
    const int row = qg * 512 + qt * 64 + warp * 16 + g;
    uint32_t* o0 = reinterpret_cast<uint32_t*>(g_o + (size_t)row * DM + head * DHEAD + q4 * 2);
    uint32_t* o1 = o0 + 8 * DM / 2;
    o0[0] = pack_bf16(O[0] * r0, O[1] * r0);  o1[0] = pack_bf16(O[2] * r1, O[3] * r1);
    o0[4] = pack_bf16(O[4] * r0, O[5] * r0);  o1[4] = pack_bf16(O[6] * r1, O[7] * r1);
    if (q4 == 0) { o0[8] = pack_bf16(O[8] * r0, O[9] * r0);  o1[8] = pack_bf16(O[10] * r1, O[11] * r1); }
  }
  TL(2, 7);
}

constexpr int K3_A = 0, K3_W = 147456, K3_X = K3_W, K3_MOD = K3_W + 9 * 9216, K3_BAR = K3_MOD + 3 * 144 + 16;
constexpr int K3_SMEM = K3_BAR + 8 * (9 + 9 + 3);

__global__ void __launch_bounds__(320, 1) k3_wo(const __grid_constant__ CUtensorMap tm_o, const __grid_constant__ CUtensorMap tm_wo,
                                                const __grid_constant__ CUtensorMap tm_x, const __grid_constant__ CUtensorMap tm_x2,
                                                const __grid_constant__ CUtensorMap tm_h2) {
  extern __shared__ __align__(1024) uint8_t smem[];
  const uint32_t sb = s2u(smem);
  const int tid = threadIdx.x, nt = blockIdx.x & 7, rb = blockIdx.x >> 3;
  const uint32_t bw = sb + K3_BAR, baf = bw + 72, bxb = baf + 72, bmd = bxb + 8, bxe = bmd + 8;
  TL(3, 0);
  if (tid == 256) {
    for (int i = 0; i < 20; i++) mbar_init(bw + 8 * i, 1);
    mbar_init(bxe, 2);
    fence_barrier_init();
    tmap_prefetch(&tm_o); tmap_prefetch(&tm_wo); tmap_prefetch(&tm_x); tmap_prefetch(&tm_x2); tmap_prefetch(&tm_h2);
  }
  __syncthreads();
  cluster_arrive_relaxed();
  pdl_launch();
  if (tid >= 288) {
    if (tid == 288)
      for (int c = 0; c < 9; c++) { mbar_expect(bw + 8 * c, 9216); tma2d(sb + K3_W + c * 9216, &tm_wo, c * 64, nt * 72, bw + 8 * c); }
    __syncwarp();
    cluster_wait();
    return;
  }
  if (tid >= 256) {
    cluster_wait();
    if (tid == 256) {
      const int rank = cluster_rank();
      pdl_wait();
      for (int c = 0; c < 9; c++) {
        mbar_expect(baf + 8 * c, 16384);
        tma2d_mc(sb + K3_A + c * 16384 + rank * 8192, &tm_o, c * 64, rb * 128 + rank * 64, baf + 8 * c);
      }
      mbar_expect(bmd, 3 * 144);
      for (int v = 0; v < 3; v++) bulk_g2s(sb + K3_MOD + v * 144, g_mod + (2 + v) * DM + nt * 72, 144, bmd);
      mbar_wait(bxe, 0);
      mbar_expect(bxb, 18432); tma2d(sb + K3_X, &tm_x, nt * 72, rb * 128, bxb);
    }
    __syncwarp();
    cluster_arrive_relaxed(); cluster_wait();
    return;
  }
  const int wg = __reduce_max_sync(0xffffffffu, (unsigned)tid >> 7), wtid = tid & 127, warp = (tid >> 5) & 3, lane = tid & 31, g = lane >> 2, q4 = lane & 3;
  const int lrow = wg * 64 + warp * 16 + g;
  cluster_wait();
  pdl_wait();
  TL(3, 1);
  const uint32_t tag = __ldcg(&g_epoch);
  float acc[36];
#pragma unroll
  for (int i = 0; i < 36; i++) acc[i] = 0.f;
  const uint64_t da0 = mkdesc(sb + K3_A + wg * 8192, 16, 1024, 1);
  const uint64_t db0 = mkdesc(sb + K3_W, 16, 1024, 1);
#pragma unroll 1
  for (int c = 0; c < 9; c++) {
    mbar_wait(bw + 8 * c, 0);
    mbar_wait(baf + 8 * c, 0);
    wg_fence();
#pragma unroll
    for (int j = 0; j < 4; j++) wgmma_ss_n72(acc, da0 + (uint64_t)(c * 1024 + j * 2), db0 + (uint64_t)(c * 576 + j * 2), 1);
    wg_commit();
    if (c == 2) { wg_wait<1>(); if (wtid == 0) mbar_arrive(bxe); }
  }
  wg_wait<0>();
  fence_regs(acc);
  cluster_arrive_relaxed();
  TL(3, 2);
  mbar_wait(bmd, 0);
  mbar_wait(bxb, 0);
  const uint32_t xa = sb + K3_X + lrow * 144 + q4 * 4, ma = sb + K3_MOD + q4 * 4;
  float s0 = 0.f, s1 = 0.f;
#pragma unroll
  for (int i = 0; i < 9; i++) {
    const uint32_t x0 = lds32(xa + 16 * i), x1 = lds32(xa + 8 * 144 + 16 * i), ga = lds32(ma + 16 * i);
    const float g0 = bf_lo(ga), g1 = bf_hi(ga);
    const uint32_t p0 = pack_bf16(fmaf(g0, acc[4 * i], bf_lo(x0)), fmaf(g1, acc[4 * i + 1], bf_hi(x0)));
    const uint32_t p1 = pack_bf16(fmaf(g0, acc[4 * i + 2], bf_lo(x1)), fmaf(g1, acc[4 * i + 3], bf_hi(x1)));
    sts32(xa + 16 * i, p0); sts32(xa + 8 * 144 + 16 * i, p1);
    acc[4 * i] = bf_lo(p0); acc[4 * i + 1] = bf_hi(p0); acc[4 * i + 2] = bf_lo(p1); acc[4 * i + 3] = bf_hi(p1);
    s0 += acc[4 * i] + acc[4 * i + 1]; s1 += acc[4 * i + 2] + acc[4 * i + 3];
  }
  s0 += __shfl_xor_sync(0xffffffffu, s0, 1); s1 += __shfl_xor_sync(0xffffffffu, s1, 1);
  s0 += __shfl_xor_sync(0xffffffffu, s0, 2); s1 += __shfl_xor_sync(0xffffffffu, s1, 2);
  const float m0 = s0 * (1.0f / 72), m1 = s1 * (1.0f / 72);
  float v0 = 0.f, v1 = 0.f;
#pragma unroll
  for (int i = 0; i < 9; i++) {
    float d;
    d = acc[4 * i] - m0; v0 = fmaf(d, d, v0); d = acc[4 * i + 1] - m0; v0 = fmaf(d, d, v0);
    d = acc[4 * i + 2] - m1; v1 = fmaf(d, d, v1); d = acc[4 * i + 3] - m1; v1 = fmaf(d, d, v1);
  }
  v0 += __shfl_xor_sync(0xffffffffu, v0, 1); v1 += __shfl_xor_sync(0xffffffffu, v1, 1);
  v0 += __shfl_xor_sync(0xffffffffu, v0, 2); v1 += __shfl_xor_sync(0xffffffffu, v1, 2);
  if (q4 < 2) {
    const float mm = q4 ? m1 : m0, vv = q4 ? v1 : v0;
    asm volatile("st.relaxed.gpu.global.v2.b64 [%0], {%1, %2};"
                 :: "l"(&g_stats[(rb * 8 + nt) * 128 + lrow + 8 * q4]), "l"(((uint64_t)tag << 32) | __float_as_uint(mm)), "l"(((uint64_t)tag << 32) | __float_as_uint(vv)) : "memory");
  }
  fence_async_smem();
  bar_sync(1, 256);
  TL(3, 3);
  if (tid == 0) { tma2d_store(&tm_x2, sb + K3_X, nt * 72, rb * 128); bulk_commit(); }
  float mean0, mean1, rs0, rs1;
  {
    uint64_t w[8];
    const uint4* pa = &g_stats[(rb * 8 + 2 * q4) * 128 + lrow];
    for (int it = 0; it < (1 << 20); it++) {
      asm volatile("ld.relaxed.gpu.global.v2.b64 {%0, %1}, [%2];" : "=l"(w[0]), "=l"(w[1]) : "l"(pa) : "memory");
      asm volatile("ld.relaxed.gpu.global.v2.b64 {%0, %1}, [%2];" : "=l"(w[2]), "=l"(w[3]) : "l"(pa + 128) : "memory");
      asm volatile("ld.relaxed.gpu.global.v2.b64 {%0, %1}, [%2];" : "=l"(w[4]), "=l"(w[5]) : "l"(pa + 8) : "memory");
      asm volatile("ld.relaxed.gpu.global.v2.b64 {%0, %1}, [%2];" : "=l"(w[6]), "=l"(w[7]) : "l"(pa + 136) : "memory");
      bool ok = true;
#pragma unroll
      for (int j = 0; j < 8; j++) ok = ok && (uint32_t)(w[j] >> 32) == tag;
      if (__all_sync(0xffffffffu, ok)) break;
      __nanosleep(200);
    }
    const float ax = __uint_as_float((uint32_t)w[0]), ay = __uint_as_float((uint32_t)w[1]), az = __uint_as_float((uint32_t)w[2]), aw = __uint_as_float((uint32_t)w[3]);
    const float bx = __uint_as_float((uint32_t)w[4]), by = __uint_as_float((uint32_t)w[5]), bz = __uint_as_float((uint32_t)w[6]), bw_ = __uint_as_float((uint32_t)w[7]);
    float sa = ax + az, sb_ = bx + bz;
    sa += __shfl_xor_sync(0xffffffffu, sa, 1); sb_ += __shfl_xor_sync(0xffffffffu, sb_, 1);
    sa += __shfl_xor_sync(0xffffffffu, sa, 2); sb_ += __shfl_xor_sync(0xffffffffu, sb_, 2);
    mean0 = sa * 0.125f; mean1 = sb_ * 0.125f;
    float ma2 = ay + aw + 72.f * ((ax - mean0) * (ax - mean0) + (az - mean0) * (az - mean0));
    float mb2 = by + bw_ + 72.f * ((bx - mean1) * (bx - mean1) + (bz - mean1) * (bz - mean1));
    ma2 += __shfl_xor_sync(0xffffffffu, ma2, 1); mb2 += __shfl_xor_sync(0xffffffffu, mb2, 1);
    ma2 += __shfl_xor_sync(0xffffffffu, ma2, 2); mb2 += __shfl_xor_sync(0xffffffffu, mb2, 2);
    rs0 = rsqrtf(ma2 * (1.0f / DM) + 1e-5f); rs1 = rsqrtf(mb2 * (1.0f / DM) + 1e-5f);
  }
  TL(3, 4);
  {
    const uint32_t ha = sb + K3_A + lrow * 144 + q4 * 4;
#pragma unroll
    for (int i = 0; i < 9; i++) {
      const uint32_t c1p = hadd2(lds32(ma + 288 + 16 * i), 0x3F803F80u), sh = lds32(ma + 144 + 16 * i);
      sts32(ha + 16 * i, hfma2(hfma2(pack_bf16((acc[4 * i] - mean0) * rs0, (acc[4 * i + 1] - mean0) * rs0), c1p, sh), 0x3F003F00u, 0x80008000u));
      sts32(ha + 8 * 144 + 16 * i, hfma2(hfma2(pack_bf16((acc[4 * i + 2] - mean1) * rs1, (acc[4 * i + 3] - mean1) * rs1), c1p, sh), 0x3F003F00u, 0x80008000u));
    }
  }
  fence_async_smem();
  bar_sync(1, 256);
  if (tid == 0) { tma2d_store(&tm_h2, sb + K3_A, nt * 72, rb * 128); bulk_commit(); bulk_wait_read(); }
  TL(3, 7);
  cluster_wait();
}

constexpr int K4_BK = 64;
constexpr int K4_KS = K4_BK / 16;
constexpr int K4_SPT = 576 / K4_BK;
constexpr int K4_NST = 3 * 64 / K4_BK;
constexpr int K4_STB = K4_BK * 384;
constexpr int K4_A = 0, K4_B = 147456, K4_BAR = K4_B + K4_NST * K4_STB, K4_SMEM = K4_BAR + 8 * (9 + 2 * K4_NST) + 8;

__device__ __forceinline__ uint32_t silu2(uint32_t v, uint32_t m16, uint32_t mhi) {
  const float lo = __uint_as_float(v * m16), hi = __uint_as_float(v & mhi);
  return pack_bf16(fmaf(lo, tanh_fast(lo), lo), fmaf(hi, tanh_fast(hi), hi));
}
template <int P>
__device__ __forceinline__ void k4_epi(const uint32_t (&pk)[48], uint32_t go, bf16* hp) {
  const uint32_t m16 = go << 16, mhi = 0u - m16;
  constexpr int B = 8 * (P >> 1) + (P & 1);
  uint4 r;
  r.x = silu2(pk[B], m16, mhi); r.y = silu2(pk[B + 2], m16, mhi); r.z = silu2(pk[B + 4], m16, mhi); r.w = silu2(pk[B + 6], m16, mhi);
  asm volatile("st.global.v4.b32 [%0], {%1,%2,%3,%4};" :: "l"(hp + (P & 1) * 8 * FF + 32 * (P >> 1)), "r"(r.x), "r"(r.y), "r"(r.z), "r"(r.w) : "memory");
}
template <int P0, int N>
__device__ __forceinline__ void k4_epi_n(const uint32_t (&pk)[48], uint32_t go, bf16* hp) {
  if constexpr (N > 0) { k4_epi<P0>(pk, go, hp); k4_epi_n<P0 + 1, N - 1>(pk, go, hp); }
}
__host__ __device__ constexpr int k4_first(int i) { return (i * 12 + 8) / 9; }

template <int T, int I>
__device__ __forceinline__ void k4_steps(float (&acc)[96], const uint32_t (&pk)[48], uint64_t da0, uint64_t db0, uint32_t ba, uint32_t bbf,
                                         uint32_t rbe, int wtid, bf16* hp) {
  if constexpr (I < K4_SPT) {
    constexpr int st = T * K4_SPT + I, s = st % K4_NST, k0 = I * K4_KS;
    if (T == 0 && (k0 & 3) == 0) mbar_wait(ba + 8 * (k0 >> 2), 0);
    mbar_wait(bbf + 8 * s, (st / K4_NST) & 1);
    wg_fence();
#pragma unroll
    for (int j = 0; j < K4_KS; j++)
      wgmma_ss_n192_tb(acc, da0 + (uint64_t)(((k0 + j) >> 2) * 1024 + ((k0 + j) & 3) * 2), db0 + (uint64_t)(s * (K4_STB / 16) + j * 128), (I | j) != 0);
    wg_commit();
    if constexpr (I > 0) {
      wg_wait<1>();
      if (st - 1 + K4_NST < 3 * K4_SPT && wtid < 2) mbar_arrive_remote(rbe + 8 * ((st - 1) % K4_NST));
    }
    if constexpr (T > 0 && k4_first(I + 1) > k4_first(I)) {
      const uint32_t go = mbar_try(ba, 0);
      k4_epi_n<k4_first(I), k4_first(I + 1) - k4_first(I)>(pk, go, hp);
    }
    k4_steps<T, I + 1>(acc, pk, da0, db0, ba, bbf, rbe, wtid, hp);
  }
}
template <int T>
__device__ __forceinline__ void k4_tile(float (&acc)[96], const uint32_t (&pk)[48], uint64_t da0, uint64_t db0, uint32_t ba, uint32_t bbf,
                                        uint32_t rbe, int wtid, bf16* hprev) {
  k4_steps<T, 0>(acc, pk, da0, db0, ba, bbf, rbe, wtid, hprev);
  wg_wait<0>();
  fence_regs(acc);
  if (T * K4_SPT + K4_SPT - 1 + K4_NST < 3 * K4_SPT && wtid < 2) mbar_arrive_remote(rbe + 8 * ((T * K4_SPT + K4_SPT - 1) % K4_NST));
}
__device__ __forceinline__ void k4_pack(const float (&acc)[96], uint32_t (&pk)[48]) {
#pragma unroll
  for (int i = 0; i < 48; i++) pk[i] = pack_bf16(acc[2 * i], acc[2 * i + 1]);
}

__global__ void __launch_bounds__(384, 1) k4_mlp1(const __grid_constant__ CUtensorMap tm_h2, const __grid_constant__ CUtensorMap tm_w1) {
  extern __shared__ __align__(1024) uint8_t smem[];
  const uint32_t sb = s2u(smem);
  const int tid = threadIdx.x, rb = blockIdx.x & 15, fs = blockIdx.x >> 4;
  const uint32_t ba = sb + K4_BAR, bbf = ba + 72, bbe = bbf + 8 * K4_NST;
  TL(4, 0);
  if (tid == 0) {
    for (int i = 0; i < 9; i++) mbar_init(ba + 8 * i, 1);
    for (int i = 0; i < K4_NST; i++) { mbar_init(bbf + 8 * i, 1); mbar_init(bbe + 8 * i, 4); }
    fence_barrier_init();
    tmap_prefetch(&tm_h2); tmap_prefetch(&tm_w1);
  }
  __syncthreads();
  cluster_arrive_relaxed();
  pdl_launch();
  if (tid < 128) {
    reg_dec<40>();
    if (tid >= 32 && tid < 64) {
      auto load_a = [&](int c) { mbar_expect(ba + 8 * c, 16384); tma2d(sb + K4_A + c * 16384, &tm_h2, c * 64, rb * 128, ba + 8 * c); };
      if (tid == 32) {
        pdl_wait();
        for (int c = 0; c < 4; c++) load_a(c);
      }
      __syncwarp();
      cluster_wait();
      if (tid == 32)
        for (int c = 4; c < 9; c++) { mbar_wait(ba + 8 * (c - 4), 0); load_a(c); }
    } else {
      cluster_wait();
      if (tid == 0) {
        const int rank = cluster_rank();
        for (int st = 0; st < 3 * K4_SPT; st++) {
          const int s = st % K4_NST, t = st / K4_SPT, i = st % K4_SPT;
          if (st >= K4_NST) mbar_wait(bbe + 8 * s, (st / K4_NST - 1) & 1);
          mbar_expect(bbf + 8 * s, K4_STB);
          for (int g = 0; g < 3; g++)
            tma2d_mc(sb + K4_B + s * K4_STB + g * (K4_STB / 3) + rank * (K4_STB / 6), &tm_w1, fs * 576 + t * 192 + g * 64, i * K4_BK + rank * (K4_BK / 2), bbf + 8 * s);
        }
        cluster_arrive_relaxed(); cluster_wait();
      }
    }
  } else {
    reg_inc<232>();
    const int wg = __reduce_max_sync(0xffffffffu, ((unsigned)tid >> 7) - 1), wtid = tid & 127, warp = (tid >> 5) & 3, lane = tid & 31;
    const uint64_t da0 = mkdesc(sb + K4_A + wg * 8192, 16, 1024, 1);
    const uint64_t db0 = mkdesc(sb + K4_B, K4_STB / 3, 1024, 1);
    cluster_wait();
    const uint32_t rbe = map_cta(bbe, wtid & 1);
    bf16* hp = g_H + (size_t)(rb * 128 + wg * 64 + warp * 16 + (lane >> 2)) * FF + fs * 576 + (lane & 3) * 8;
    float acc[96]; uint32_t pk[48];
#pragma unroll
    for (int i = 0; i < 96; i++) acc[i] = 0.f;
    TLT(4, 1, 128); TLC(4, 3, 128);
    k4_tile<0>(acc, pk, da0, db0, ba, bbf, rbe, wtid, hp);
    k4_pack(acc, pk);
    k4_tile<1>(acc, pk, da0, db0, ba, bbf, rbe, wtid, hp);
    k4_pack(acc, pk);
    k4_tile<2>(acc, pk, da0, db0, ba, bbf, rbe, wtid, hp + 192);
    cluster_arrive_relaxed();
    TLT(4, 2, 128); TLC(4, 4, 128);
    k4_pack(acc, pk);
    k4_epi_n<0, 12>(pk, 1u, hp + 384);
    TLT(4, 7, 128);
    cluster_wait();
  }
}

constexpr int K5_NST = 4;
constexpr int K5_STAGE = 16384 + 36864;
constexpr int K5_GB = K5_NST * K5_STAGE, K5_BAR = K5_GB + 576, K5_SMEM = K5_BAR + 8 * (2 * K5_NST + 1);

template <int I> __device__ __forceinline__ float k5_acc(const float (&a)[128], const float (&b)[16]) { if constexpr (I < 128) return a[I]; else return b[I - 128]; }

template <int J, int I>
__device__ __forceinline__ void k5_stage(const float (&a)[128], const float (&b)[16], uint32_t dst, uint32_t gbs, int g) {
  constexpr int NB = J < 4 ? 8 : 4;
  if constexpr (I < NB) {
    constexpr int B = 8 * J + I, PITCH = J < 4 ? 128 : 64;
    const uint32_t gb = lds32(gbs + B * 16);
    const float g0 = bf_lo(gb), g1 = bf_hi(gb);
    const uint32_t sw = (uint32_t)(J < 4 ? (I ^ g) : (I ^ (g >> 1))) << 4;
    sts32(dst + sw, pack_bf16(k5_acc<4 * B>(a, b) * g0, k5_acc<4 * B + 1>(a, b) * g1));
    sts32(dst + 8 * PITCH + sw, pack_bf16(k5_acc<4 * B + 2>(a, b) * g0, k5_acc<4 * B + 3>(a, b) * g1));
    k5_stage<J, I + 1>(a, b, dst, gbs, g);
  }
}
template <int J>
__device__ __forceinline__ void k5_piece(const float (&a)[128], const float (&b)[16], uint32_t sb, uint32_t gbs, int wg, int warp, int g, int q4, int wtid,
                                         const CUtensorMap* tm, int col, int row) {
  constexpr int PITCH = J < 4 ? 128 : 64;
  const uint32_t base = sb + J * 16384 + wg * 8192;
  k5_stage<J, 0>(a, b, base + (warp * 16 + g) * PITCH + q4 * 4, gbs, g);
  fence_async_smem();
  bar_sync(2 + wg, 128);
  if (wtid == 0) {
    asm volatile("cp.reduce.async.bulk.tensor.2d.global.shared::cta.add.tile.bulk_group [%0, {%2, %3}], [%1];"
                 :: "l"(tm), "r"(base), "r"(col + J * 64), "r"(row) : "memory");
    bulk_commit();
  }
}

__global__ void __launch_bounds__(384, 1) k5_mlp2(const __grid_constant__ CUtensorMap tm_h, const __grid_constant__ CUtensorMap tm_w2,
                                                  const __grid_constant__ CUtensorMap tm_w2n, const __grid_constant__ CUtensorMap tm_out,
                                                  const __grid_constant__ CUtensorMap tm_outn) {
  extern __shared__ __align__(1024) uint8_t smem[];
  const uint32_t sb = s2u(smem);
  const int tid = threadIdx.x, rb = blockIdx.x & 15, nh = (blockIdx.x >> 4) & 1, ks = blockIdx.x >> 5;
  const uint32_t bf = sb + K5_BAR, be = bf + 8 * K5_NST, bg = be + 8 * K5_NST;
  TL(5, 0);
  if (tid == 0) {
    for (int i = 0; i < K5_NST; i++) { mbar_init(bf + 8 * i, 1); mbar_init(be + 8 * i, 4); }
    mbar_init(bg, 1);
    fence_barrier_init();
    tmap_prefetch(&tm_h); tmap_prefetch(&tm_w2); tmap_prefetch(&tm_w2n); tmap_prefetch(&tm_out); tmap_prefetch(&tm_outn);
  }
  __syncthreads();
  cluster_arrive_relaxed(); cluster_wait();
  const int rank = cluster_rank();
  if (tid < 128) {
    reg_dec<40>();
    if (tid == 0) {
      auto load_b = [&](int st) {
        const int s = st % K5_NST;
        mbar_expect(bf + 8 * s, K5_STAGE);
        for (int g = 2 * rank; g < 2 * rank + 2; g++)
          tma5d_mc(sb + s * K5_STAGE + 16384 + g * 8192, &tm_w2, nh * 288 + g * 64, 0, 0, 0, (ks * 18 + st) * 2, bf + 8 * s);
        if (rank == 1) tma5d_mc(sb + s * K5_STAGE + 16384 + 32768, &tm_w2n, nh * 288 + 256, 0, 0, 0, (ks * 18 + st) * 2, bf + 8 * s);
      };
      load_b(0);
      pdl_wait();
      for (int st = 0; st < 18; st++) {
        const int s = st % K5_NST;
        if (st >= K5_NST) mbar_wait(be + 8 * s, (st / K5_NST - 1) & 1);
        if (st >= 1) load_b(st);
        tma2d(sb + s * K5_STAGE, &tm_h, (ks * 18 + st) * 64, rb * 128, bf + 8 * s);
        if (st == K5_NST) { mbar_expect(bg, 576); bulk_g2s(sb + K5_GB, g_mod + 5 * DM + nh * 288, 576, bg); }
      }
      cluster_arrive_relaxed(); cluster_wait();
    }
  } else {
    reg_inc<232>();
    const int ctid = tid - 128, wg = __reduce_max_sync(0xffffffffu, (unsigned)ctid >> 7), wtid = tid & 127, warp = (tid >> 5) & 3, lane = tid & 31, g = lane >> 2, q4 = lane & 3;
    float a[128], b[16];
#pragma unroll
    for (int i = 0; i < 128; i++) a[i] = 0.f;
#pragma unroll
    for (int i = 0; i < 16; i++) b[i] = 0.f;
    const uint64_t db0 = mkdesc(sb + 16384, 8192, 1024, 1);
    const uint64_t dn0 = mkdesc(sb + 16384 + 32768, 4096, 512, 2);
    const uint32_t rbe = map_cta(be, wtid & 1);
    uint32_t aoff[4];
    {
      const int r = wg * 64 + warp * 16 + (lane & 7) + ((lane >> 3) & 1) * 8;
#pragma unroll
      for (int j = 0; j < 4; j++) aoff[j] = sb + r * 128 + (((2 * j + (lane >> 4)) ^ (lane & 7)) << 4);
    }
    uint32_t A0[4][4], A1[4][4];
    auto step = [&](uint32_t (&A)[4][4], int st) {
      const int s = st % K5_NST;
      mbar_wait(bf + 8 * s, (st / K5_NST) & 1);
#pragma unroll
      for (int j = 0; j < 4; j++) ldsm4(A[j], aoff[j] + s * K5_STAGE);
      fence_regs(A[0]); fence_regs(A[1]); fence_regs(A[2]); fence_regs(A[3]);
      wg_fence();
#pragma unroll
      for (int j = 0; j < 4; j++) {
        wgmma_rs_n256_tb(a, A[j][0], A[j][1], A[j][2], A[j][3], db0 + (uint64_t)(s * (K5_STAGE / 16) + j * 128), 1);
        wgmma_rs_n32_tb(b, A[j][0], A[j][1], A[j][2], A[j][3], dn0 + (uint64_t)(s * (K5_STAGE / 16) + j * 64), 1);
      }
      wg_commit();
      if (st > 0) {
        wg_wait<1>();
        if (st - 1 + K5_NST < 18 && wtid < 2) mbar_arrive_remote(rbe + 8 * ((st - 1) % K5_NST));
      }
    };
#pragma unroll 1
    for (int st = 0; st < 18; st += 2) { step(A0, st); step(A1, st + 1); }
    wg_wait<0>();
    fence_regs(a); fence_regs(b);
    cluster_arrive_relaxed();
    TLT(5, 2, 128);
    mbar_wait(bg, 0);
    bar_sync(1, 256);
    const uint32_t gbs = sb + K5_GB + q4 * 4;
    const int col0 = nh * 288, row0 = rb * 128 + wg * 64;
    k5_piece<0>(a, b, sb, gbs, wg, warp, g, q4, wtid, &tm_out, col0, row0);
    k5_piece<1>(a, b, sb, gbs, wg, warp, g, q4, wtid, &tm_out, col0, row0);
    k5_piece<2>(a, b, sb, gbs, wg, warp, g, q4, wtid, &tm_out, col0, row0);
    k5_piece<3>(a, b, sb, gbs, wg, warp, g, q4, wtid, &tm_out, col0, row0);
    k5_piece<4>(a, b, sb, gbs, wg, warp, g, q4, wtid, &tm_outn, col0, row0);
    TLT(5, 3, 128);
    if (wtid == 0) bulk_wait_read();
    TLT(5, 7, 128);
    cluster_wait();
  }
}

}

typedef CUresult (*EncodeTiledFn)(CUtensorMap*, CUtensorMapDataType, cuuint32_t, void*, const cuuint64_t*, const cuuint64_t*, const cuuint32_t*,
                                  const cuuint32_t*, CUtensorMapInterleave, CUtensorMapSwizzle, CUtensorMapL2promotion, CUtensorMapFloatOOBfill);

static void make_map2d(EncodeTiledFn enc, CUtensorMap* m, const void* base, int cols, int rows, int box_cols, int box_rows, CUtensorMapSwizzle sw) {
  cuuint64_t dims[2] = {(cuuint64_t)cols, (cuuint64_t)rows};
  cuuint64_t strides[1] = {(cuuint64_t)cols * 2};
  cuuint32_t box[2] = {(cuuint32_t)box_cols, (cuuint32_t)box_rows};
  cuuint32_t es[2] = {1, 1};
  enc(m, CU_TENSOR_MAP_DATA_TYPE_BFLOAT16, 2, const_cast<void*>(base), dims, strides, box, es, CU_TENSOR_MAP_INTERLEAVE_NONE, sw,
      CU_TENSOR_MAP_L2_PROMOTION_L2_128B, CU_TENSOR_MAP_FLOAT_OOB_FILL_NONE);
}

template <typename... KArgs, typename... Args>
static void launch(void (*kern)(KArgs...), int grid, int block, int smem, bool pdl, int cluster, Args... args) {
  cudaLaunchConfig_t cfg = {};
  cfg.gridDim = dim3(grid); cfg.blockDim = dim3(block); cfg.dynamicSmemBytes = smem; cfg.stream = cudaStreamPerThread;
  cudaLaunchAttribute at[2];
  int n = 0;
  if (pdl) { at[n].id = cudaLaunchAttributeProgrammaticStreamSerialization; at[n].val.programmaticStreamSerializationAllowed = 1; n++; }
  if (cluster > 1) { at[n].id = cudaLaunchAttributeClusterDimension; at[n].val.clusterDim.x = cluster; at[n].val.clusterDim.y = 1; at[n].val.clusterDim.z = 1; n++; }
  cfg.attrs = at; cfg.numAttrs = n;
  cudaLaunchKernelEx(&cfg, kern, KArgs(args)...);
}

#define USE_PDL 1

extern "C" void kernel_launch(void* const* d_in, const int* in_sizes, int n_in, void* d_out, int out_size) {
  (void)in_sizes; (void)n_in; (void)out_size;
  const bf16* x    = (const bf16*)d_in[0];
  const bf16* wqkv = (const bf16*)d_in[1];
  const bf16* wo   = (const bf16*)d_in[2];
  const bf16* w1   = (const bf16*)d_in[4];
  const bf16* w2   = (const bf16*)d_in[5];
  const bf16* c    = (const bf16*)d_in[6];
  const bf16* wmod = (const bf16*)d_in[7];
  bf16* out = (bf16*)d_out;

  static EncodeTiledFn enc = nullptr;
  if (!enc) {
    void* fn = nullptr; cudaDriverEntryPointQueryResult qr;
    cudaGetDriverEntryPoint("cuTensorMapEncodeTiled", &fn, cudaEnableDefault, &qr);
    enc = (EncodeTiledFn)fn;
    cudaFuncSetAttribute(k1_qkv, cudaFuncAttributeMaxDynamicSharedMemorySize, K1_SMEM);
    cudaFuncSetAttribute(k2_attn, cudaFuncAttributeMaxDynamicSharedMemorySize, K2_SMEM);
    cudaFuncSetAttribute(k3_wo, cudaFuncAttributeMaxDynamicSharedMemorySize, K3_SMEM);
    cudaFuncSetAttribute(k4_mlp1, cudaFuncAttributeMaxDynamicSharedMemorySize, K4_SMEM);
    cudaFuncSetAttribute(k5_mlp2, cudaFuncAttributeMaxDynamicSharedMemorySize, K5_SMEM);
  }
  void *p_arena, *p_woT;
  cudaGetSymbolAddress(&p_arena, g_arena); cudaGetSymbolAddress(&p_woT, g_woT);
  void* p_h2 = p_arena;
  void* p_xn = (uint8_t*)p_arena + 96 * SLOT_BYTES;
  void* p_o = p_xn;
  void* p_H = (uint8_t*)p_arena + ACT_BYTES;
  CUtensorMap tm_xn, tm_wqkv, tm_o, tm_wo, tm_x, tm_x2s, tm_h2s, tm_h2, tm_w1, tm_H, tm_w2, tm_w2n, tm_out, tm_outn, tm_wmod;
  make_map2d(enc, &tm_xn, p_xn, DM, SEQ, 64, 128, CU_TENSOR_MAP_SWIZZLE_128B);
  make_map2d(enc, &tm_wqkv, wqkv, 3 * DM, DM, 64, 32, CU_TENSOR_MAP_SWIZZLE_128B);
  make_map2d(enc, &tm_o, p_o, DM, SEQ, 64, 64, CU_TENSOR_MAP_SWIZZLE_128B);
  make_map2d(enc, &tm_x, x, DM, SEQ, 72, 128, CU_TENSOR_MAP_SWIZZLE_NONE);
  make_map2d(enc, &tm_wmod, wmod, 6 * DM, DM, 192, 64, CU_TENSOR_MAP_SWIZZLE_NONE);
  make_map2d(enc, &tm_x2s, out, DM, SEQ, 72, 128, CU_TENSOR_MAP_SWIZZLE_NONE);
  make_map2d(enc, &tm_out, out, DM, SEQ, 64, 64, CU_TENSOR_MAP_SWIZZLE_128B);
  make_map2d(enc, &tm_outn, out, DM, SEQ, 32, 64, CU_TENSOR_MAP_SWIZZLE_64B);
  make_map2d(enc, &tm_h2s, p_h2, DM, SEQ, 72, 128, CU_TENSOR_MAP_SWIZZLE_NONE);
  make_map2d(enc, &tm_wo, p_woT, DM, DM, 64, 72, CU_TENSOR_MAP_SWIZZLE_128B);
  make_map2d(enc, &tm_h2, p_h2, DM, SEQ, 64, 128, CU_TENSOR_MAP_SWIZZLE_128B);
  make_map2d(enc, &tm_w1, w1, FF, DM, 64, K4_BK / 2, CU_TENSOR_MAP_SWIZZLE_128B);
  make_map2d(enc, &tm_H, p_H, FF, SEQ, 64, 128, CU_TENSOR_MAP_SWIZZLE_128B);
  for (int narrow = 0; narrow < 2; narrow++) {
    cuuint64_t dims[5] = {(cuuint64_t)DM, 2, 4, 4, (cuuint64_t)(FF / 32)};
    cuuint64_t strides[4] = {(cuuint64_t)DM * 2, (cuuint64_t)DM * 2 * 8, (cuuint64_t)DM * 2 * 2, (cuuint64_t)DM * 2 * 32};
    cuuint32_t box[5] = {narrow ? 32u : 64u, 2, 4, 4, 2};
    cuuint32_t es[5] = {1, 1, 1, 1, 1};
    enc(narrow ? &tm_w2n : &tm_w2, CU_TENSOR_MAP_DATA_TYPE_BFLOAT16, 5, const_cast<bf16*>(w2), dims, strides, box, es, CU_TENSOR_MAP_INTERLEAVE_NONE,
        narrow ? CU_TENSOR_MAP_SWIZZLE_64B : CU_TENSOR_MAP_SWIZZLE_128B, CU_TENSOR_MAP_L2_PROMOTION_L2_128B, CU_TENSOR_MAP_FLOAT_OOB_FILL_NONE);
  }
  launch(k0_mod_ln, 36 * MODP + 128, 256, 0, false, 1, x, c, wmod, wqkv);
  launch(k1_qkv, 128, 352, K1_SMEM, USE_PDL, 2, tm_xn, tm_wqkv, wo);
  launch(k2_attn, 132, 512, K2_SMEM, USE_PDL, 1, tm_wmod, c, w1, w2);
  launch(k3_wo, 128, 320, K3_SMEM, USE_PDL, 2, tm_o, tm_wo, tm_x, tm_x2s, tm_h2s);
  launch(k4_mlp1, 128, 384, K4_SMEM, USE_PDL, 2, tm_h2, tm_w1);
  launch(k5_mlp2, 128, 384, K5_SMEM, USE_PDL, 2, tm_H, tm_w2, tm_w2n, tm_out, tm_outn);
}
```
